```python
import torch

def _softmax(x, axis=-1):
    return torch.softmax(x, dim=axis)
def _gelu(x):
    return torch.nn.functional.gelu(x, approximate="tanh")
def _silu(x):
    return torch.nn.functional.silu(x)
def _sigmoid(x):
    return torch.sigmoid(x)
def _layernorm(x, axis=-1, eps=1e-5):
    m = x.mean(dim=axis, keepdim=True)
    v = x.var(dim=axis, keepdim=True, unbiased=False)
    return (x - m) / torch.sqrt(v + eps)
def _scatter_add(tgt, idx, src, axis=0):
    return tgt.clone().index_add_(axis, idx, src)
def _segment_sum(src, seg, n):
    out = torch.zeros((n,) + src.shape[1:], dtype=src.dtype)
    return out.index_add_(0, seg, src)
def _pad(x, pw):
    flat = tuple(v for pair in reversed(pw) for v in pair)
    return torch.nn.functional.pad(x, flat)

kernel_name = 'sequential_preLN__spectral_gfnet__moe_arch_mod__prompt'

def setup_inputs():

    _w = (lambda a: (lambda t: t.to(torch.bfloat16) if t.is_floating_point() else t)(torch.as_tensor(a)))
    def _A_setup():
        B, S, D = 1, 2048, 1024
        Df = D // 2 + 1
        return {
            "x": _w((lambda *s: torch.randn(*s, dtype=torch.bfloat16) * 0.05)(B, S, D)),
            "w_r": _w((lambda *s: torch.randn(*s, dtype=torch.bfloat16) * 0.4)(S, Df) * 0.02),
            "w_i": _w((lambda *s: torch.randn(*s, dtype=torch.bfloat16) * 0.4)(S, Df) * 0.02),
        }
    _A_in = _A_setup()

    def _B_setup():
        B, S, D, F, C = 1, 2048, 1024, 3584, 1
        return {
            "x": _w((lambda *s: torch.randn(*s, dtype=torch.bfloat16) * 0.05)(B, S, D)),
            "w_r": _w((lambda *s: torch.randn(*s, dtype=torch.bfloat16) * 0.2)(D)),
            "w_gate": _w((lambda *s: torch.randn(*s, dtype=torch.bfloat16) * 0.2)(D, F)),
            "w_up": _w((lambda *s: torch.randn(*s, dtype=torch.bfloat16) * 0.2)(D, F)),
            "w_down": _w((lambda *s: torch.randn(*s, dtype=torch.bfloat16) * 0.2)(F, D)),
        }
    _B_in = _B_setup()

    return {
        "A_x": _A_in["x"],
        "A_w_r": _A_in["w_r"],
        "A_w_i": _A_in["w_i"],
        "B_x": _B_in["x"],
        "B_w_r": _B_in["w_r"],
        "B_w_gate": _B_in["w_gate"],
        "B_w_up": _B_in["w_up"],
        "B_w_down": _B_in["w_down"],
    }

def reference(A_x, A_w_r, A_w_i, B_x, B_w_r, B_w_gate, B_w_up, B_w_down):
    def _A_ref(x, w_r, w_i):
        B, S, D = x.shape
        X = (lambda x, axes=(-2,-1): torch.fft.rfft2(x.float(), dim=axes))(x, axes=(-2, -1))
        W = w_r + 1j * w_i
        X = X * W
        y = (lambda x, s, axes=(-2,-1): torch.fft.irfft2(x, s=s, dim=axes).to(torch.bfloat16))(X, (S, D), axes=(-2, -1))
        return y

    def _B_ref(x, w_r, w_gate, w_up, w_down):
        B, S, D = x.shape
        C = 1
        r = x @ w_r
        idx = torch.argsort(-r, axis=-1)[:, :C]
        idx_e = (lambda x, n, axis: torch.repeat_interleave(x, n, dim=axis))(idx.reshape(B, C, 1), D, axis=2)
        x_sel = (lambda x, i, axis: torch.take_along_dim(x, i, dim=axis))(x, idx_e, axis=1)
        g = _silu(x_sel @ w_gate)
        u = x_sel @ w_up
        y = (g * u) @ w_down
        r_sel = _sigmoid((lambda x, i, axis: torch.take_along_dim(x, i, dim=axis))(r, idx, axis=1))
        y = y * r_sel.reshape(B, C, 1)
        b_off = (torch.arange(B) * S).reshape(B, 1)
        flat_idx = (idx + b_off).reshape(B * C)
        zero = (x * 0.0).reshape(B * S, D)
        upd = _scatter_add(zero, flat_idx, y.reshape(B * C, D), axis=0)
        return x + upd.reshape(B, S, D)

    x = A_x
    h = x + _A_ref(_layernorm(x, axis=-1), A_w_r, A_w_i)
    h2 = h + _B_ref(_layernorm(h, axis=-1), B_w_r, B_w_gate, B_w_up, B_w_down)
    return h2
```

```cpp
#include <cuda_runtime.h>
#include <cuda_bf16.h>
#include <cuda_fp16.h>
#include <cuda.h>
#include <stdint.h>

typedef unsigned int u32;
typedef unsigned long long u64;

#define NCTA 128
#define NFFN 112
#define NTHR 384
#define SM_GU 0
#define SM_TAB 49152
#define SM_TAB2 151552
#define SM_W 114688
#define SM_D0 131072
#define SM_D1 163840
#define SM_E 196608
#define SM_MISC 229888
#define SM_TOTAL 232448
#define E_P 1040
#define E_A 8320
#define MB_X 0
#define MB_W 8
#define MB_IN2 9
#define MB_IN3 11
#define MB_ST1 13
#define MB_ST2 15
#define MB_SC 18
#define MB_GU 19
#define MB_DN 20
#define MB_AM 21
#define MB_D1F 22
#define MB_TGT 17
#define MB_INIT 23
#define MB_F0 292
#define MB_WC 26
#define MB_KEY 27
#define MB_OUT 28
#define MB_PS 30
#define NMB 31
#define MB_TAB 31
#define MS_WIN 2304
#define MS_KEY 2528
#define MS_EXP 2528
#define MS_PART 256

#define FILL_W 4
#define DN_EARLY 1
#define FILL_T0 1000
#define SPEC_MIN 64
#define SUSP_NS 4000
#define RHELP 56
#define RCOMP 224

struct __align__(1024) Scratch {
    u32 cnt1[64];
    u64 wmax[16];
    u32 cnt2[64];
    u64 amax[16];
    u32 cnt3[64];
    uint4 s1[NCTA * 2048];
    uint4 s2[NCTA * 2048];
    uint4 n1[16 * 128 * 2];
    uint4 n2[128 * 16 * 2];
    u32 cand[NCTA * 1024];
    float part[NCTA * NFFN * 8];
};
__device__ Scratch g_s;

__device__ const __align__(16) u32 g_tab[2816] = {
0x34003400,0xb4003400,0x34003400,0xb4003400,0x34003400,0xb4003400,0x34003400,0xb4003400,0x34003400,0xb4003400,0x34003400,0xb4003400,0x34003400,0xb4003400,0x34003400,0xb4003400,
0x33643400,0xb3643400,0xb364b400,0x3364b400,0x2e1f31a8,0xae1f31a8,0xae1fb1a8,0x2e1fb1a8,0xae1f0000,0x2e1f0000,0x2e1f0000,0xae1f0000,0xb364b1a8,0x3364b1a8,0x336431a8,0xb36431a8,
0x31a83400,0xb1a83400,0x31a83400,0xb1a83400,0xb1a80000,0x31a80000,0xb1a80000,0x31a80000,0xb1a8b400,0x31a8b400,0xb1a8b400,0x31a8b400,0x31a80000,0xb1a80000,0x31a80000,0xb1a80000,
0x2e1f3400,0xae1f3400,0xae1fb400,0x2e1fb400,0xb364b1a8,0x3364b1a8,0x336431a8,0xb36431a8,0x33640000,0xb3640000,0xb3640000,0x33640000,0xae1f31a8,0x2e1f31a8,0x2e1fb1a8,0xae1fb1a8,
0x3400,0x3400,0x3400,0x3400,0xb400,0xb400,0xb400,0xb400,0x3400,0x3400,0x3400,0x3400,0xb400,0xb400,0xb400,0xb400,
0xae1f3400,0x2e1f3400,0x2e1fb400,0xae1fb400,0x3364b1a8,0xb364b1a8,0xb36431a8,0x336431a8,0xb3640000,0x33640000,0x33640000,0xb3640000,0x2e1f31a8,0xae1f31a8,0xae1fb1a8,0x2e1fb1a8,
0xb1a83400,0x31a83400,0xb1a83400,0x31a83400,0x31a80000,0xb1a80000,0x31a80000,0xb1a80000,0x31a8b400,0xb1a8b400,0x31a8b400,0xb1a8b400,0xb1a80000,0x31a80000,0xb1a80000,0x31a80000,
0xb3643400,0x33643400,0x3364b400,0xb364b400,0xae1f31a8,0x2e1f31a8,0x2e1fb1a8,0xae1fb1a8,0x2e1f0000,0xae1f0000,0xae1f0000,0x2e1f0000,0x3364b1a8,0xb364b1a8,0xb36431a8,0x336431a8,
0x0,0x0,0x0,0x0,0x0,0x0,0x0,0x0,0x0,0x0,0x0,0x0,0x0,0x0,0x0,0x0,
0xae1f0000,0x2e1f0000,0x2e1f0000,0xae1f0000,0xb364b1a8,0x3364b1a8,0x336431a8,0xb36431a8,0xb364b400,0x3364b400,0x33643400,0xb3643400,0xae1fb1a8,0x2e1fb1a8,0x2e1f31a8,0xae1f31a8,
0xb1a80000,0x31a80000,0xb1a80000,0x31a80000,0xb1a8b400,0x31a8b400,0xb1a8b400,0x31a8b400,0x31a80000,0xb1a80000,0x31a80000,0xb1a80000,0x31a83400,0xb1a83400,0x31a83400,0xb1a83400,
0xb3640000,0x33640000,0x33640000,0xb3640000,0x2e1fb1a8,0xae1fb1a8,0xae1f31a8,0x2e1f31a8,0x2e1f3400,0xae1f3400,0xae1fb400,0x2e1fb400,0xb364b1a8,0x3364b1a8,0x336431a8,0xb36431a8,
0xb4000000,0x34000000,0xb4000000,0x34000000,0x34000000,0xb4000000,0x34000000,0xb4000000,0xb4000000,0x34000000,0xb4000000,0x34000000,0x34000000,0xb4000000,0x34000000,0xb4000000,
0xb3640000,0x33640000,0x33640000,0xb3640000,0x2e1f31a8,0xae1f31a8,0xae1fb1a8,0x2e1fb1a8,0x2e1fb400,0xae1fb400,0xae1f3400,0x2e1f3400,0xb36431a8,0x336431a8,0x3364b1a8,0xb364b1a8,
0xb1a80000,0x31a80000,0xb1a80000,0x31a80000,0xb1a83400,0x31a83400,0xb1a83400,0x31a83400,0x31a80000,0xb1a80000,0x31a80000,0xb1a80000,0x31a8b400,0xb1a8b400,0x31a8b400,0xb1a8b400,
0xae1f0000,0x2e1f0000,0x2e1f0000,0xae1f0000,0xb36431a8,0x336431a8,0x3364b1a8,0xb364b1a8,0xb3643400,0x33643400,0x3364b400,0xb364b400,0xae1f31a8,0x2e1f31a8,0x2e1fb1a8,0xae1fb1a8,
0x80008000,0x80008000,0x80008000,0x80008000,0x80008000,0x80008000,0x80008000,0x80008000,0x80008000,0x80008000,0x80008000,0x80008000,0x80008000,0x80008000,0x80008000,0x80008000,
0x2e1f8000,0xae1f8000,0xae1f8000,0x2e1f8000,0x336431a8,0xb36431a8,0xb364b1a8,0x3364b1a8,0x33643400,0xb3643400,0xb364b400,0x3364b400,0x2e1f31a8,0xae1f31a8,0xae1fb1a8,0x2e1fb1a8,
0x31a88000,0xb1a88000,0x31a88000,0xb1a88000,0x31a83400,0xb1a83400,0x31a83400,0xb1a83400,0xb1a88000,0x31a88000,0xb1a88000,0x31a88000,0xb1a8b400,0x31a8b400,0xb1a8b400,0x31a8b400,
0x33648000,0xb3648000,0xb3648000,0x33648000,0xae1f31a8,0x2e1f31a8,0x2e1fb1a8,0xae1fb1a8,0xae1fb400,0x2e1fb400,0x2e1f3400,0xae1f3400,0x336431a8,0xb36431a8,0xb364b1a8,0x3364b1a8,
0x34008000,0xb4008000,0x34008000,0xb4008000,0xb4008000,0x34008000,0xb4008000,0x34008000,0x34008000,0xb4008000,0x34008000,0xb4008000,0xb4008000,0x34008000,0xb4008000,0x34008000,
0x33648000,0xb3648000,0xb3648000,0x33648000,0xae1fb1a8,0x2e1fb1a8,0x2e1f31a8,0xae1f31a8,0xae1f3400,0x2e1f3400,0x2e1fb400,0xae1fb400,0x3364b1a8,0xb364b1a8,0xb36431a8,0x336431a8,
0x31a88000,0xb1a88000,0x31a88000,0xb1a88000,0x31a8b400,0xb1a8b400,0x31a8b400,0xb1a8b400,0xb1a88000,0x31a88000,0xb1a88000,0x31a88000,0xb1a83400,0x31a83400,0xb1a83400,0x31a83400,
0x2e1f8000,0xae1f8000,0xae1f8000,0x2e1f8000,0x3364b1a8,0xb364b1a8,0xb36431a8,0x336431a8,0x3364b400,0xb364b400,0xb3643400,0x33643400,0x2e1fb1a8,0xae1fb1a8,0xae1f31a8,0x2e1f31a8,
0x3c003c00,0x3b643c00,0x0,0xb61f0000,0x3c003c00,0x361f39a8,0x0,0xbb64b9a8,0x3c003c00,0xb61f0000,0x0,0xbb64bc00,0x3c003c00,0xbb64b9a8,0x0,0xb61fb9a8,
0x3bfe3c00,0x3b3b3c00,0xaa480000,0xb6d70000,0x3bea3bf6,0x33c63913,0xb0b2ae46,0xbbc3ba2f,0x3bc33bd9,0xb8c4b23e,0xb3c6b23e,0xba6dbbd9,0x3b883ba8,0xbbfebb0e,0xb564b4a5,0xaa48b78b,
0x3bf63c00,0x3b0e3c00,0xae460000,0xb78b0000,0x3ba83bd9,0x2e463872,0xb4a5b23e,0xbbf6baa7,0x3b0e3b64,0xba2fb61f,0xb78bb61f,0xb913bb64,0x3a2f3aa7,0xbba8bbd9,0xb913b872,0x34a5b23e,
0x3bea3c00,0x3add3c00,0xb0b20000,0xb81d0000,0x3b3b3ba8,0xaa48378b,0xb6d7b4a5,0xbbfebb0e,0x39ed3aa7,0xbb3bb872,0xb95fb872,0xb6d7baa7,0x381d3913,0xba6dbbf6,0xbaddba2f,0x38c42e46,
0x3bd93c00,0x3aa73c00,0xb23e0000,0xb8720000,0x3aa73b64,0xb23e361f,0xb872b61f,0xbbd9bb64,0x387239a8,0xbbd9b9a8,0xbaa7b9a8,0xb23eb9a8,0x323e361f,0xb872bb64,0xbbd9bb64,0x3aa7361f,
0x3bc33c00,0x3a6d3c00,0xb3c60000,0xb8c40000,0x39ed3b0e,0xb56434a5,0xb95fb78b,0xbb88bba8,0x35643872,0xbbfebaa7,0xbb88baa7,0x2a48b872,0xb0b22e46,0xb3c6ba2f,0xbbeabbf6,0x3bc33913,
0x3ba83c00,0x3a2f3c00,0xb4a50000,0xb9130000,0x39133aa7,0xb78b323e,0xba2fb872,0xbb0ebbd9,0x2e46361f,0xbba8bb64,0xbbf6bb64,0x34a5b61f,0xb78bb23e,0x2e46b872,0xbb0ebbd9,0x3bf63aa7,
0x3b883c00,0x39ed3c00,0xb5640000,0xb95f0000,0x381d3a2f,0xb8c42e46,0xbaddb913,0xba6dbbf6,0xb0b2323e,0xbaddbbd9,0xbbeabbd9,0x381db23e,0xb9edb78b,0x36d7b4a5,0xb95fbb0e,0x3b3b3ba8,
0x38003800,0x0,0x80008000,0x0,0x38003800,0x0,0x80008000,0x0,0x38003800,0x0,0x80008000,0x0,0x38003800,0x0,0x80008000,0x0,
0xb8003800,0x0,0x80008000,0x0,0xb8003800,0x0,0x80008000,0x0,0xb8003800,0x0,0x80008000,0x0,0xb8003800,0x0,0x80008000,0x0,
0x35a83800,0xb5a80000,0x35a88000,0x0,0xb5a80000,0xb5a8b800,0x35a83800,0x0,0xb5a8b800,0x35a80000,0xb5a88000,0x0,0x35a80000,0x35a83800,0xb5a8b800,0x0,
0xb5a83800,0x35a80000,0xb5a88000,0x0,0x35a80000,0x35a8b800,0xb5a83800,0x0,0x35a8b800,0xb5a80000,0x35a88000,0x0,0xb5a80000,0xb5a83800,0x35a8b800,0x0,
0x3800,0xb8000000,0x38008000,0x0,0xb800,0x38000000,0xb8008000,0x0,0x3800,0xb8000000,0x38008000,0x0,0xb800,0x38000000,0xb8008000,0x0,
0x3800,0x38000000,0xb8008000,0x0,0xb800,0xb8000000,0x38008000,0x0,0x3800,0x38000000,0xb8008000,0x0,0xb800,0xb8000000,0x38008000,0x0,
0xb5a83800,0xb5a80000,0x35a88000,0x0,0x35a80000,0xb5a83800,0x35a8b800,0x0,0x35a8b800,0x35a80000,0xb5a88000,0x0,0xb5a80000,0x35a8b800,0xb5a83800,0x0,
0x35a83800,0x35a80000,0xb5a88000,0x0,0xb5a80000,0x35a83800,0xb5a8b800,0x0,0xb5a8b800,0xb5a80000,0x35a88000,0x0,0x35a80000,0xb5a8b800,0x35a83800,0x0,
0x3bfe3c00,0x3b3b3b64,0xaa480000,0xb6d7b61f,0x3bea3bf6,0x3add3b0e,0xb0b2ae46,0xb81db78b,0x3bc33bd9,0x3a6d3aa7,0xb3c6b23e,0xb8c4b872,0x3b883ba8,0x39ed3a2f,0xb564b4a5,0xb95fb913,
0x3bfd3c00,0x3b363b5f,0xab119e48,0xb6eeb637,0x3be83bf5,0x3ad63b08,0xb0e4aeaa,0xb828b7a1,0x3bc03bd6,0x3a653aa0,0xb3f7b26f,0xb8ceb87c,0x3b843ba4,0x39e53a27,0xb57cb4bd,0xb969b91d,
0x3bfc3c00,0x3b303b5a,0xabd9a248,0xb705b64e,0x3be63bf4,0x3ad03b02,0xb115af0e,0xb832b7b7,0x3bbc3bd4,0x3a5e3a99,0xb414b2a1,0xb8d8b887,0x3b803ba0,0x39dc3a1f,0xb593b4d5,0xb972b927,
0x3bfb3c00,0x3b2b3b55,0xac51a4b6,0xb71bb665,0x3be43bf2,0x3ac93afc,0xb147af72,0xb83db7cd,0x3bb93bd1,0x3a563a92,0xb42cb2d2,0xb8e2b891,0x3b7b3b9d,0x39d43a17,0xb5abb4ed,0xb97bb930,
0x3bfa3bff,0x3b253b50,0xacb5a648,0xb732b67c,0x3be23bf1,0x3ac23af6,0xb179afd6,0xb848b7e3,0x3bb63bce,0x3a4f3a8a,0xb444b303,0xb8ecb89b,0x3b773b99,0x39cb3a0f,0xb5c2b505,0xb984b93a,
0x3bf93bff,0x3b203b4b,0xad1aa7da,0xb748b693,0x3be03bef,0x3abc3af0,0xb1aab01d,0xb852b7f9,0x3bb23bcb,0x3a473a83,0xb45db334,0xb8f6b8a6,0x3b723b95,0x39c33a07,0xb5dab51d,0xb98db943,
0x3bf83bff,0x3b1a3b46,0xad7ea8b6,0xb75eb6aa,0x3bdd3bed,0x3ab53ae9,0xb1dbb04e,0xb85db807,0x3baf3bc9,0x3a3f3a7c,0xb475b365,0xb900b8b0,0x3b6e3b91,0x39ba39fe,0xb5f1b534,0xb996b94d,
0x3bf73bfe,0x3b143b41,0xade2a97f,0xb775b6c1,0x3bdb3bec,0x3aae3ae3,0xb20db080,0xb867b812,0x3bab3bc6,0x3a373a74,0xb48db396,0xb909b8ba,0x3b693b8c,0x39b139f6,0xb608b54c,0xb99fb956,
0x3bf63c00,0x391339a8,0xae460000,0xba2fb9a8,0x3ba83bd9,0x378b3872,0xb4a5b23e,0xbb0ebaa7,0x3b0e3b64,0x34a5361f,0xb78bb61f,0xbba8bb64,0x3a2f3aa7,0x2e46323e,0xb913b872,0xbbf6bbd9,
0x3bf43c00,0x39003996,0xaf0ea248,0xba3fb9ba,0x3ba03bd4,0x375e385d,0xb4d5b2a1,0xbb1abab5,0x3b023b5a,0x347535f1,0xb7b7b64e,0xbbafbb6e,0x3a1f3a99,0x2d7e31db,0xb927b887,0xbbf8bbdd,
0x3bf13bff,0x38ec3984,0xafd6a648,0xba4fb9cb,0x3b993bce,0x37323848,0xb505b303,0xbb25bac2,0x3af63b50,0x344435c2,0xb7e3b67c,0xbbb6bb77,0x3a0f3a8a,0x2cb53179,0xb93ab89b,0xbbfabbe2,
0x3bed3bff,0x38d83972,0xb04ea8b6,0xba5eb9dc,0x3b913bc9,0x37053832,0xb534b365,0xbb30bad0,0x3ae93b46,0x34143593,0xb807b6aa,0xbbbcbb80,0x39fe3a7c,0x2bd93115,0xb94db8b0,0xbbfcbbe6,
0x3bea3bfe,0x38c4395f,0xb0b2aa48,0xba6db9ed,0x3b883bc3,0x36d7381d,0xb564b3c6,0xbb3bbadd,0x3add3b3b,0x33c63564,0xb81db6d7,0xbbc3bb88,0x39ed3a6d,0x2a4830b2,0xb95fb8c4,0xbbfebbea,
0x3be63bfc,0x38b0394d,0xb115abd9,0xba7cb9fe,0x3b803bbc,0x36aa3807,0xb593b414,0xbb46bae9,0x3ad03b30,0x33653534,0xb832b705,0xbbc9bb91,0x39dc3a5e,0x28b6304e,0xb972b8d8,0xbbffbbed,
0x3be23bfa,0x389b393a,0xb179acb5,0xba8aba0f,0x3b773bb6,0x367c37e3,0xb5c2b444,0xbb50baf6,0x3ac23b25,0x33033505,0xb848b732,0xbbcebb99,0x39cb3a4f,0x26482fd6,0xb984b8ec,0xbbffbbf1,
0x3bdd3bf8,0x38873927,0xb1dbad7e,0xba99ba1f,0x3b6e3baf,0x364e37b7,0xb5f1b475,0xbb5abb02,0x3ab53b1a,0x32a134d5,0xb85db75e,0xbbd4bba0,0x39ba3a3f,0x22482f0e,0xb996b900,0xbc00bbf4,
0x3bea3c00,0x33c6361f,0xb0b20000,0xbbc3bb64,0x3b3b3ba8,0xaa482e46,0xb6d7b4a5,0xbbfebbf6,0x39ed3aa7,0xb564b23e,0xb95fb872,0xbb88bbd9,0x381d3913,0xb8c4b78b,0xbaddba2f,0xba6dbb0e,
0x3be43c00,0x333435da,0xb147a4b6,0xbbcbbb72,0x3b2b3b9d,0xac512d1a,0xb71bb4ed,0xbbfbbbf9,0x39d43a92,0xb5abb2d2,0xb97bb891,0xbb7bbbd1,0x37f938f6,0xb8e2b7cd,0xbaf0ba47,0xba56bafc,
0x3bdd3bff,0x32a13593,0xb1dba8b6,0xbbd4bb80,0x3b1a3b91,0xad7e2bd9,0xb75eb534,0xbbf8bbfc,0x39ba3a7c,0xb5f1b365,0xb996b8b0,0xbb6ebbc9,0x37b738d8,0xb900b807,0xbb02ba5e,0xba3fbae9,
0x3bd63bfd,0x320d354c,0xb26fab11,0xbbdbbb8c,0x3b083b84,0xaeaa297f,0xb7a1b57c,0xbbf5bbfe,0x399f3a65,0xb637b3f7,0xb9b1b8ce,0xbb5fbbc0,0x377538ba,0xb91db828,0xbb14ba74,0xba27bad6,
0x3bce3bfa,0x31793505,0xb303acb5,0xbbe2bb99,0x3af63b77,0xafd62648,0xb7e3b5c2,0xbbf1bbff,0x39843a4f,0xb67cb444,0xb9cbb8ec,0xbb50bbb6,0x3732389b,0xb93ab848,0xbb25ba8a,0xba0fbac2,
0x3bc63bf7,0x30e434bd,0xb396ade2,0xbbe8bba4,0x3ae33b69,0xb0801e48,0xb812b608,0xbbecbc00,0x39693a37,0xb6c1b48d,0xb9e5b909,0xbb41bbab,0x36ee387c,0xb956b867,0xbb36baa0,0xb9f6baae,
0x3bbc3bf4,0x304e3475,0xb414af0e,0xbbedbbaf,0x3ad03b5a,0xb115a248,0xb832b64e,0xbbe6bc00,0x394d3a1f,0xb705b4d5,0xb9feb927,0xbb30bba0,0x36aa385d,0xb972b887,0xbb46bab5,0xb9dcba99,
0x3bb23bef,0x2f72342c,0xb45db01d,0xbbf2bbb9,0x3abc3b4b,0xb1aaa7da,0xb852b693,0xbbe0bbff,0x39303a07,0xb748b51d,0xba17b943,0xbb20bb95,0x3665383d,0xb98db8a6,0xbb55bac9,0xb9c3ba83,
0x3bd93c00,0xb23e0000,0xb23e0000,0xbbd9bc00,0x3aa73b64,0xb872b61f,0xb872b61f,0xbaa7bb64,0x387239a8,0xbaa7b9a8,0xbaa7b9a8,0xb872b9a8,0x323e361f,0xbbd9bb64,0xbbd9bb64,0xb23eb61f,
0x3bce3bff,0xb303a648,0xb303a648,0xbbcebbff,0x3a8a3b50,0xb89bb67c,0xb89bb67c,0xba8abb50,0x38483984,0xbac2b9cb,0xbac2b9cb,0xb848b984,0x317935c2,0xbbe2bb77,0xbbe2bb77,0xb179b5c2,
0x3bc33bfe,0xb3c6aa48,0xb3c6aa48,0xbbc3bbfe,0x3a6d3b3b,0xb8c4b6d7,0xb8c4b6d7,0xba6dbb3b,0x381d395f,0xbaddb9ed,0xbaddb9ed,0xb81db95f,0x30b23564,0xbbeabb88,0xbbeabb88,0xb0b2b564,
0x3bb63bfa,0xb444acb5,0xb444acb5,0xbbb6bbfa,0x3a4f3b25,0xb8ecb732,0xb8ecb732,0xba4fbb25,0x37e3393a,0xbaf6ba0f,0xbaf6ba0f,0xb7e3b93a,0x2fd63505,0xbbf1bb99,0xbbf1bb99,0xafd6b505,
0x3ba83bf6,0xb4a5ae46,0xb4a5ae46,0xbba8bbf6,0x3a2f3b0e,0xb913b78b,0xb913b78b,0xba2fbb0e,0x378b3913,0xbb0eba2f,0xbb0eba2f,0xb78bb913,0x2e4634a5,0xbbf6bba8,0xbbf6bba8,0xae46b4a5,
0x3b993bf1,0xb505afd6,0xb505afd6,0xbb99bbf1,0x3a0f3af6,0xb93ab7e3,0xb93ab7e3,0xba0fbaf6,0x373238ec,0xbb25ba4f,0xbb25ba4f,0xb732b8ec,0x2cb53444,0xbbfabbb6,0xbbfabbb6,0xacb5b444,
0x3b883bea,0xb564b0b2,0xb564b0b2,0xbb88bbea,0x39ed3add,0xb95fb81d,0xb95fb81d,0xb9edbadd,0x36d738c4,0xbb3bba6d,0xbb3bba6d,0xb6d7b8c4,0x2a4833c6,0xbbfebbc3,0xbbfebbc3,0xaa48b3c6,
0x3b773be2,0xb5c2b179,0xb5c2b179,0xbb77bbe2,0x39cb3ac2,0xb984b848,0xb984b848,0xb9cbbac2,0x367c389b,0xbb50ba8a,0xbb50ba8a,0xb67cb89b,0x26483303,0xbbffbbce,0xbbffbbce,0xa648b303,
0x3bc33c00,0xb8c4b61f,0xb3c60000,0xba6dbb64,0x39ed3b0e,0xbb3bba2f,0xb95fb78b,0xb6d7b913,0x35643872,0xbbfebbd9,0xbb88baa7,0x2a48b23e,0xb0b22e46,0xbaddbba8,0xbbeabbf6,0x381d34a5,
0x3bb23bff,0xb8f6b693,0xb45da7da,0xba47bb4b,0x39c33af0,0xbb55ba56,0xb98db7f9,0xb665b8e2,0x34ed383d,0xbbf9bbe4,0xbb9dbac9,0x2d1ab147,0xb1aa2c51,0xbabcbb95,0xbbe0bbfb,0x3852351d,
0x3ba03bfc,0xb927b705,0xb4d5abd9,0xba1fbb30,0x39963ad0,0xbb6eba7c,0xb9bab832,0xb5f1b8b0,0x34753807,0xbbf4bbed,0xbbafbae9,0x2f0eb04e,0xb2a128b6,0xba99bb80,0xbbd4bbff,0x38873593,
0x3b8c3bf7,0xb956b775,0xb54cade2,0xb9f6bb14,0x39693aae,0xbb84baa0,0xb9e5b867,0xb57cb87c,0x33f737a1,0xbbecbbf5,0xbbc0bb08,0x3080aeaa,0xb3961e48,0xba74bb69,0xbbc6bc00,0x38ba3608,
0x3b773bf1,0xb984b7e3,0xb5c2afd6,0xb9cbbaf6,0x393a3a8a,0xbb99bac2,0xba0fb89b,0xb505b848,0x33033732,0xbbe2bbfa,0xbbcebb25,0x3179acb5,0xb444a648,0xba4fbb50,0xbbb6bbff,0x38ec367c,
0x3b5f3be8,0xb9b1b828,0xb637b0e4,0xb99fbad6,0x39093a65,0xbbabbae3,0xba37b8ce,0xb48db812,0x320d36c1,0xbbd6bbfe,0xbbdbbb41,0x326fa97f,0xb4bdab11,0xba27bb36,0xbba4bbfd,0x391d36ee,
0x3b463bdd,0xb9dcb85d,0xb6aab1db,0xb972bab5,0x38d83a3f,0xbbbcbb02,0xba5eb900,0xb414b7b7,0x3115364e,0xbbc9bc00,0xbbe6bb5a,0x3365a248,0xb534ad7e,0xb9febb1a,0xbb91bbf8,0x394d375e,
0x3b2b3bd1,0xba07b891,0xb71bb2d2,0xb943ba92,0x38a63a17,0xbbcbbb20,0xba83b930,0xb334b748,0x301d35da,0xbbb9bc00,0xbbefbb72,0x342c24b6,0xb5abaf72,0xb9d4bafc,0xbb7bbbf2,0x397b37cd,
0x3ba83c00,0xbb0eb9a8,0xb4a50000,0xb78bb9a8,0x39133aa7,0xbbf6bbd9,0xba2fb872,0x2e46b23e,0x2e46361f,0xba2fbb64,0xbbf6bb64,0x3913361f,0xb78bb23e,0xb4a5b872,0xbb0ebbd9,0x3ba83aa7,
0x3b913bff,0xbb30b9dc,0xb534a8b6,0xb705b972,0x38d83a7c,0xbbedbbe6,0xba5eb8b0,0x304eb115,0x2bd93593,0xb9febb46,0xbbfcbb80,0x394d36aa,0xb807b365,0xb414b832,0xbae9bbc9,0x3bbc3ad0,
0x3b773bfa,0xbb50ba0f,0xb5c2acb5,0xb67cb93a,0x389b3a4f,0xbbe2bbf1,0xba8ab8ec,0x3179afd6,0x26483505,0xb9cbbb25,0xbbffbb99,0x39843732,0xb848b444,0xb303b7e3,0xbac2bbb6,0x3bce3af6,
0x3b5a3bf4,0xbb6eba3f,0xb64eaf0e,0xb5f1b900,0x385d3a1f,0xbbd4bbf8,0xbab5b927,0x32a1ad7e,0xa2483475,0xb996bb02,0xbc00bbaf,0x39ba37b7,0xb887b4d5,0xb1dbb75e,0xba99bba0,0x3bdd3b1a,
0x3b3b3bea,0xbb88ba6d,0xb6d7b0b2,0xb564b8c4,0x381d39ed,0xbbc3bbfe,0xbaddb95f,0x33c6aa48,0xaa4833c6,0xb95fbadd,0xbbfebbc3,0x39ed381d,0xb8c4b564,0xb0b2b6d7,0xba6dbb88,0x3bea3b3b,
0x3b1a3bdd,0xbba0ba99,0xb75eb1db,0xb4d5b887,0x37b739ba,0xbbafbc00,0xbb02b996,0x3475a248,0xad7e32a1,0xb927bab5,0xbbf8bbd4,0x3a1f385d,0xb900b5f1,0xaf0eb64e,0xba3fbb6e,0x3bf43b5a,
0x3af63bce,0xbbb6bac2,0xb7e3b303,0xb444b848,0x37323984,0xbb99bbff,0xbb25b9cb,0x35052648,0xafd63179,0xb8ecba8a,0xbbf1bbe2,0x3a4f389b,0xb93ab67c,0xacb5b5c2,0xba0fbb50,0x3bfa3b77,
0x3ad03bbc,0xbbc9bae9,0xb832b414,0xb365b807,0x36aa394d,0xbb80bbfc,0xbb46b9fe,0x35932bd9,0xb115304e,0xb8b0ba5e,0xbbe6bbed,0x3a7c38d8,0xb972b705,0xa8b6b534,0xb9dcbb30,0x3bff3b91,
0x3b883c00,0xbbfebb64,0xb5640000,0xaa48b61f,0x381d3a2f,0xba6dbba8,0xbaddb913,0x38c434a5,0xb0b2323e,0xb3c6b872,0xbbeabbd9,0x3bc33aa7,0xb9edb78b,0x36d72e46,0xb95fbb0e,0x3b3b3bf6,
0x3b693bfe,0xbc00bb84,0xb608a97f,0x9e48b57c,0x37a139f6,0xba37bb8c,0xbb08b956,0x3909354c,0xb20d30e4,0xb26fb828,0xbbdbbbe8,0x3bd63ad6,0xba27b812,0x37753080,0xb91dbae3,0x3b143bec,
0x3b463bf8,0xbbffbba0,0xb6aaad7e,0x28b6b4d5,0x370539ba,0xb9febb6e,0xbb30b996,0x394d35f1,0xb3652f0e,0xb115b7b7,0xbbc9bbf4,0x3be63b02,0xba5eb85d,0x380731db,0xb8d8bab5,0x3ae93bdd,
0x3b203bef,0xbbf9bbb9,0xb748b01d,0x2d1ab42c,0x3665397b,0xb9c3bb4b,0xbb55b9d4,0x398d3693,0xb45d2c51,0xaf72b71b,0xbbb2bbfb,0x3bf23b2b,0xba92b8a6,0x38523334,0xb891ba83,0x3abc3bcb,
0x3af63be2,0xbbf1bbce,0xb7e3b179,0x2fd6b303,0x35c2393a,0xb984bb25,0xbb77ba0f,0x39cb3732,0xb5052648,0xacb5b67c,0xbb99bbff,0x3bfa3b50,0xbac2b8ec,0x389b3444,0xb848ba4f,0x3a8a3bb6,
0x3ac93bd1,0xbbe4bbe0,0xb83db2d2,0x3147b1aa,0x351d38f6,0xb943bafc,0xbb95ba47,0x3a0737cd,0xb5aba4b6,0xa7dab5da,0xbb7bbc00,0x3bff3b72,0xbaf0b930,0x38e234ed,0xb7f9ba17,0x3a563b9d,
0x3a993bbc,0xbbd4bbed,0xb887b414,0x32a1b04e,0x347538b0,0xb900bad0,0xbbafba7c,0x3a3f3832,0xb64eabd9,0x2248b534,0xbb5abbfc,0x3c003b91,0xbb1ab972,0x39273593,0xb75eb9dc,0x3a1f3b80,
0x3a653ba4,0xbbc0bbf7,0xb8ceb4bd,0x33f7ade2,0x33963867,0xb8babaa0,0xbbc6baae,0x3a74387c,0xb6eeaeaa,0x2b11b48d,0xbb36bbf5,0x3bfd3bab,0xbb41b9b1,0x39693637,0xb6c1b99f,0x39e53b5f,
0x38003800,0x0,0x80008000,0x0,0x38003800,0x0,0x80008000,0x0,0x38003800,0x0,0x80008000,0x0,0x38003800,0x0,0x80008000,0x0,
0x35a83800,0xb5a80000,0x35a88000,0x0,0xb5a80000,0xb5a8b800,0x35a83800,0x0,0xb5a8b800,0x35a80000,0xb5a88000,0x0,0x35a80000,0x35a83800,0xb5a8b800,0x0,
0x3800,0xb8000000,0x38008000,0x0,0xb800,0x38000000,0xb8008000,0x0,0x3800,0xb8000000,0x38008000,0x0,0xb800,0x38000000,0xb8008000,0x0,
0xb5a83800,0xb5a80000,0x35a88000,0x0,0x35a80000,0xb5a83800,0x35a8b800,0x0,0x35a8b800,0x35a80000,0xb5a88000,0x0,0xb5a80000,0x35a8b800,0xb5a83800,0x0,
0xb8003800,0x0,0x80008000,0x0,0xb8003800,0x0,0x80008000,0x0,0xb8003800,0x0,0x80008000,0x0,0xb8003800,0x0,0x80008000,0x0,
0xb5a83800,0x35a80000,0xb5a88000,0x0,0x35a80000,0x35a8b800,0xb5a83800,0x0,0x35a8b800,0xb5a80000,0x35a88000,0x0,0xb5a80000,0xb5a83800,0x35a8b800,0x0,
0x3800,0x38000000,0xb8008000,0x0,0xb800,0xb8000000,0x38008000,0x0,0x3800,0x38000000,0xb8008000,0x0,0xb800,0xb8000000,0x38008000,0x0,
0x35a83800,0x35a80000,0xb5a88000,0x0,0xb5a80000,0x35a83800,0xb5a8b800,0x0,0xb5a8b800,0xb5a80000,0x35a88000,0x0,0x35a80000,0xb5a8b800,0x35a83800,0x0,
0x3c003c00,0x3c003c00,0x0,0x0,0x3c003c00,0x3c003c00,0x0,0x0,0x3c003c00,0x3c003c00,0x0,0x0,0x3c003c00,0x3c003c00,0x0,0x0,
0x3bfe3c00,0x3b3b3b64,0xaa480000,0xb6d7b61f,0x3bea3bf6,0x3add3b0e,0xb0b2ae46,0xb81db78b,0x3bc33bd9,0x3a6d3aa7,0xb3c6b23e,0xb8c4b872,0x3b883ba8,0x39ed3a2f,0xb564b4a5,0xb95fb913,
0x3bf63c00,0x391339a8,0xae460000,0xba2fb9a8,0x3ba83bd9,0x378b3872,0xb4a5b23e,0xbb0ebaa7,0x3b0e3b64,0x34a5361f,0xb78bb61f,0xbba8bb64,0x3a2f3aa7,0x2e46323e,0xb913b872,0xbbf6bbd9,
0x3bea3c00,0x33c6361f,0xb0b20000,0xbbc3bb64,0x3b3b3ba8,0xaa482e46,0xb6d7b4a5,0xbbfebbf6,0x39ed3aa7,0xb564b23e,0xb95fb872,0xbb88bbd9,0x381d3913,0xb8c4b78b,0xbaddba2f,0xba6dbb0e,
0x3bd93c00,0xb23e0000,0xb23e0000,0xbbd9bc00,0x3aa73b64,0xb872b61f,0xb872b61f,0xbaa7bb64,0x387239a8,0xbaa7b9a8,0xbaa7b9a8,0xb872b9a8,0x323e361f,0xbbd9bb64,0xbbd9bb64,0xb23eb61f,
0x3bc33c00,0xb8c4b61f,0xb3c60000,0xba6dbb64,0x39ed3b0e,0xbb3bba2f,0xb95fb78b,0xb6d7b913,0x35643872,0xbbfebbd9,0xbb88baa7,0x2a48b23e,0xb0b22e46,0xbaddbba8,0xbbeabbf6,0x381d34a5,
0x3ba83c00,0xbb0eb9a8,0xb4a50000,0xb78bb9a8,0x39133aa7,0xbbf6bbd9,0xba2fb872,0x2e46b23e,0x2e46361f,0xba2fbb64,0xbbf6bb64,0x3913361f,0xb78bb23e,0xb4a5b872,0xbb0ebbd9,0x3ba83aa7,
0x3b883c00,0xbbfebb64,0xb5640000,0xaa48b61f,0x381d3a2f,0xba6dbba8,0xbaddb913,0x38c434a5,0xb0b2323e,0xb3c6b872,0xbbeabbd9,0x3bc33aa7,0xb9edb78b,0x36d72e46,0xb95fbb0e,0x3b3b3bf6,
0x38003800,0x0,0x80008000,0x0,0x38003800,0x0,0x80008000,0x0,0x38003800,0x0,0x80008000,0x0,0x38003800,0x0,0x80008000,0x0,
0xb8003800,0x0,0x80008000,0x0,0xb5a835a8,0x35a8b5a8,0xb5a835a8,0x0,0x0,0x3800b800,0xb8003800,0x0,0x35a8b5a8,0x35a8b5a8,0xb5a835a8,0x0,
0x38003800,0x0,0x80008000,0x0,0x0,0xb800b800,0x38003800,0x0,0xb800b800,0x0,0x80008000,0x0,0x0,0x38003800,0xb800b800,0x0,
0xb8003800,0x0,0x80008000,0x0,0x35a8b5a8,0x35a8b5a8,0xb5a835a8,0x0,0x0,0xb8003800,0x3800b800,0x0,0xb5a835a8,0x35a8b5a8,0xb5a835a8,0x0,
0x38003800,0x0,0x80008000,0x0,0xb800b800,0x0,0x80008000,0x0,0x38003800,0x0,0x80008000,0x0,0xb800b800,0x0,0x80008000,0x0,
0xb8003800,0x0,0x80008000,0x0,0x35a8b5a8,0xb5a835a8,0x35a8b5a8,0x0,0x0,0x3800b800,0xb8003800,0x0,0xb5a835a8,0xb5a835a8,0x35a8b5a8,0x0,
0x38003800,0x0,0x80008000,0x0,0x0,0x38003800,0xb800b800,0x0,0xb800b800,0x0,0x80008000,0x0,0x0,0xb800b800,0x38003800,0x0,
0xb8003800,0x0,0x80008000,0x0,0xb5a835a8,0xb5a835a8,0x35a8b5a8,0x0,0x0,0xb8003800,0x3800b800,0x0,0x35a8b5a8,0xb5a835a8,0x35a8b5a8,0x0,
0x3c003c00,0x3b5f3b64,0x9e480000,0xb637b61f,0x3c003c00,0x3b553b5a,0xa4b6a248,0xb665b64e,0x3bff3bff,0x3b4b3b50,0xa7daa648,0xb693b67c,0x3bfe3bff,0x3b413b46,0xa97fa8b6,0xb6c1b6aa,
0x3bfd3bfe,0x3b363b3b,0xab11aa48,0xb6eeb6d7,0x3bfb3bfc,0x3b2b3b30,0xac51abd9,0xb71bb705,0x3bf93bfa,0x3b203b25,0xad1aacb5,0xb748b732,0x3bf73bf8,0x3b143b1a,0xade2ad7e,0xb775b75e,
0x3bf53bf6,0x3b083b0e,0xaeaaae46,0xb7a1b78b,0x3bf23bf4,0x3afc3b02,0xaf72af0e,0xb7cdb7b7,0x3bef3bf1,0x3af03af6,0xb01dafd6,0xb7f9b7e3,0x3bec3bed,0x3ae33ae9,0xb080b04e,0xb812b807,
0x3be83bea,0x3ad63add,0xb0e4b0b2,0xb828b81d,0x3be43be6,0x3ac93ad0,0xb147b115,0xb83db832,0x3be03be2,0x3abc3ac2,0xb1aab179,0xb852b848,0x3bdb3bdd,0x3aae3ab5,0xb20db1db,0xb867b85d,
0x3bd63bd9,0x3aa03aa7,0xb26fb23e,0xb87cb872,0x3bd13bd4,0x3a923a99,0xb2d2b2a1,0xb891b887,0x3bcb3bce,0x3a833a8a,0xb334b303,0xb8a6b89b,0x3bc63bc9,0x3a743a7c,0xb396b365,0xb8bab8b0,
0x3bc03bc3,0x3a653a6d,0xb3f7b3c6,0xb8ceb8c4,0x3bb93bbc,0x3a563a5e,0xb42cb414,0xb8e2b8d8,0x3bb23bb6,0x3a473a4f,0xb45db444,0xb8f6b8ec,0x3bab3baf,0x3a373a3f,0xb48db475,0xb909b900,
0x3ba43ba8,0x3a273a2f,0xb4bdb4a5,0xb91db913,0x3b9d3ba0,0x3a173a1f,0xb4edb4d5,0xb930b927,0x3b953b99,0x3a073a0f,0xb51db505,0xb943b93a,0x3b8c3b91,0x39f639fe,0xb54cb534,0xb956b94d,
0x3b843b88,0x39e539ed,0xb57cb564,0xb969b95f,0x3b7b3b80,0x39d439dc,0xb5abb593,0xb97bb972,0x3b723b77,0x39c339cb,0xb5dab5c2,0xb98db984,0x3b693b6e,0x39b139ba,0xb608b5f1,0xb99fb996,
0x3c003c00,0x399639a8,0xa2480000,0xb9bab9a8,0x3bff3bff,0x39723984,0xa8b6a648,0xb9dcb9cb,0x3bfc3bfe,0x394d395f,0xabd9aa48,0xb9feb9ed,0x3bf83bfa,0x3927393a,0xad7eacb5,0xba1fba0f,
0x3bf43bf6,0x39003913,0xaf0eae46,0xba3fba2f,0x3bed3bf1,0x38d838ec,0xb04eafd6,0xba5eba4f,0x3be63bea,0x38b038c4,0xb115b0b2,0xba7cba6d,0x3bdd3be2,0x3887389b,0xb1dbb179,0xba99ba8a,
0x3bd43bd9,0x385d3872,0xb2a1b23e,0xbab5baa7,0x3bc93bce,0x38323848,0xb365b303,0xbad0bac2,0x3bbc3bc3,0x3807381d,0xb414b3c6,0xbae9badd,0x3baf3bb6,0x37b737e3,0xb475b444,0xbb02baf6,
0x3ba03ba8,0x375e378b,0xb4d5b4a5,0xbb1abb0e,0x3b913b99,0x37053732,0xb534b505,0xbb30bb25,0x3b803b88,0x36aa36d7,0xb593b564,0xbb46bb3b,0x3b6e3b77,0x364e367c,0xb5f1b5c2,0xbb5abb50,
0x3b5a3b64,0x35f1361f,0xb64eb61f,0xbb6ebb64,0x3b463b50,0x359335c2,0xb6aab67c,0xbb80bb77,0x3b303b3b,0x35343564,0xb705b6d7,0xbb91bb88,0x3b1a3b25,0x34d53505,0xb75eb732,0xbba0bb99,
0x3b023b0e,0x347534a5,0xb7b7b78b,0xbbafbba8,0x3ae93af6,0x34143444,0xb807b7e3,0xbbbcbbb6,0x3ad03add,0x336533c6,0xb832b81d,0xbbc9bbc3,0x3ab53ac2,0x32a13303,0xb85db848,0xbbd4bbce,
0x3a993aa7,0x31db323e,0xb887b872,0xbbddbbd9,0x3a7c3a8a,0x31153179,0xb8b0b89b,0xbbe6bbe2,0x3a5e3a6d,0x304e30b2,0xb8d8b8c4,0xbbedbbea,0x3a3f3a4f,0x2f0e2fd6,0xb900b8ec,0xbbf4bbf1,
0x3a1f3a2f,0x2d7e2e46,0xb927b913,0xbbf8bbf6,0x39fe3a0f,0x2bd92cb5,0xb94db93a,0xbbfcbbfa,0x39dc39ed,0x28b62a48,0xb972b95f,0xbbffbbfe,0x39ba39cb,0x22482648,0xb996b984,0xbc00bbff,
0x3c003c00,0x35da361f,0xa4b60000,0xbb72bb64,0x3bfd3bff,0x354c3593,0xab11a8b6,0xbb8cbb80,0x3bf73bfa,0x34bd3505,0xade2acb5,0xbba4bb99,0x3bef3bf4,0x342c3475,0xb01daf0e,0xbbb9bbaf,
0x3be43bea,0x333433c6,0xb147b0b2,0xbbcbbbc3,0x3bd63bdd,0x320d32a1,0xb26fb1db,0xbbdbbbd4,0x3bc63bce,0x30e43179,0xb396b303,0xbbe8bbe2,0x3bb23bbc,0x2f72304e,0xb45db414,0xbbf2bbed,
0x3b9d3ba8,0x2d1a2e46,0xb4edb4a5,0xbbf9bbf6,0x3b843b91,0x297f2bd9,0xb57cb534,0xbbfebbfc,0x3b693b77,0x1e482648,0xb608b5c2,0xbc00bbff,0x3b4b3b5a,0xa7daa248,0xb693b64e,0xbbffbc00,
0x3b2b3b3b,0xac51aa48,0xb71bb6d7,0xbbfbbbfe,0x3b083b1a,0xaeaaad7e,0xb7a1b75e,0xbbf5bbf8,0x3ae33af6,0xb080afd6,0xb812b7e3,0xbbecbbf1,0x3abc3ad0,0xb1aab115,0xb852b832,0xbbe0bbe6,
0x3a923aa7,0xb2d2b23e,0xb891b872,0xbbd1bbd9,0x3a653a7c,0xb3f7b365,0xb8ceb8b0,0xbbc0bbc9,0x3a373a4f,0xb48db444,0xb909b8ec,0xbbabbbb6,0x3a073a1f,0xb51db4d5,0xb943b927,0xbb95bba0,
0x39d439ed,0xb5abb564,0xb97bb95f,0xbb7bbb88,0x399f39ba,0xb637b5f1,0xb9b1b996,0xbb5fbb6e,0x39693984,0xb6c1b67c,0xb9e5b9cb,0xbb41bb50,0x3930394d,0xb748b705,0xba17b9fe,0xbb20bb30,
0x38f63913,0xb7cdb78b,0xba47ba2f,0xbafcbb0e,0x38ba38d8,0xb828b807,0xba74ba5e,0xbad6bae9,0x387c389b,0xb867b848,0xbaa0ba8a,0xbaaebac2,0x383d385d,0xb8a6b887,0xbac9bab5,0xba83ba99,
0x37f9381d,0xb8e2b8c4,0xbaf0badd,0xba56ba6d,0x377537b7,0xb91db900,0xbb14bb02,0xba27ba3f,0x36ee3732,0xb956b93a,0xbb36bb25,0xb9f6ba0f,0x366536aa,0xb98db972,0xbb55bb46,0xb9c3b9dc,
0x3bff3c00,0xa6480000,0xa6480000,0xbbffbc00,0x3bfa3bfe,0xacb5aa48,0xacb5aa48,0xbbfabbfe,0x3bf13bf6,0xafd6ae46,0xafd6ae46,0xbbf1bbf6,0x3be23bea,0xb179b0b2,0xb179b0b2,0xbbe2bbea,
0x3bce3bd9,0xb303b23e,0xb303b23e,0xbbcebbd9,0x3bb63bc3,0xb444b3c6,0xb444b3c6,0xbbb6bbc3,0x3b993ba8,0xb505b4a5,0xb505b4a5,0xbb99bba8,0x3b773b88,0xb5c2b564,0xb5c2b564,0xbb77bb88,
0x3b503b64,0xb67cb61f,0xb67cb61f,0xbb50bb64,0x3b253b3b,0xb732b6d7,0xb732b6d7,0xbb25bb3b,0x3af63b0e,0xb7e3b78b,0xb7e3b78b,0xbaf6bb0e,0x3ac23add,0xb848b81d,0xb848b81d,0xbac2badd,
0x3a8a3aa7,0xb89bb872,0xb89bb872,0xba8abaa7,0x3a4f3a6d,0xb8ecb8c4,0xb8ecb8c4,0xba4fba6d,0x3a0f3a2f,0xb93ab913,0xb93ab913,0xba0fba2f,0x39cb39ed,0xb984b95f,0xb984b95f,0xb9cbb9ed,
0x398439a8,0xb9cbb9a8,0xb9cbb9a8,0xb984b9a8,0x393a395f,0xba0fb9ed,0xba0fb9ed,0xb93ab95f,0x38ec3913,0xba4fba2f,0xba4fba2f,0xb8ecb913,0x389b38c4,0xba8aba6d,0xba8aba6d,0xb89bb8c4,
0x38483872,0xbac2baa7,0xbac2baa7,0xb848b872,0x37e3381d,0xbaf6badd,0xbaf6badd,0xb7e3b81d,0x3732378b,0xbb25bb0e,0xbb25bb0e,0xb732b78b,0x367c36d7,0xbb50bb3b,0xbb50bb3b,0xb67cb6d7,
0x35c2361f,0xbb77bb64,0xbb77bb64,0xb5c2b61f,0x35053564,0xbb99bb88,0xbb99bb88,0xb505b564,0x344434a5,0xbbb6bba8,0xbbb6bba8,0xb444b4a5,0x330333c6,0xbbcebbc3,0xbbcebbc3,0xb303b3c6,
0x3179323e,0xbbe2bbd9,0xbbe2bbd9,0xb179b23e,0x2fd630b2,0xbbf1bbea,0xbbf1bbea,0xafd6b0b2,0x2cb52e46,0xbbfabbf6,0xbbfabbf6,0xacb5ae46,0x26482a48,0xbbffbbfe,0xbbffbbfe,0xa648aa48,
0x3bff3c00,0xb693b61f,0xa7da0000,0xbb4bbb64,0x3bf73bfc,0xb775b705,0xade2abd9,0xbb14bb30,0x3be83bf1,0xb828b7e3,0xb0e4afd6,0xbad6baf6,0x3bd13bdd,0xb891b85d,0xb2d2b1db,0xba92bab5,
0x3bb23bc3,0xb8f6b8c4,0xb45db3c6,0xba47ba6d,0x3b8c3ba0,0xb956b927,0xb54cb4d5,0xb9f6ba1f,0x3b5f3b77,0xb9b1b984,0xb637b5c2,0xb99fb9cb,0x3b2b3b46,0xba07b9dc,0xb71bb6aa,0xb943b972,
0x3af03b0e,0xba56ba2f,0xb7f9b78b,0xb8e2b913,0x3aae3ad0,0xbaa0ba7c,0xb867b832,0xb87cb8b0,0x3a653a8a,0xbae3bac2,0xb8ceb89b,0xb812b848,0x3a173a3f,0xbb20bb02,0xb930b900,0xb748b7b7,
0x39c339ed,0xbb55bb3b,0xb98db95f,0xb665b6d7,0x39693996,0xbb84bb6e,0xb9e5b9ba,0xb57cb5f1,0x3909393a,0xbbabbb99,0xba37ba0f,0xb48db505,0x38a638d8,0xbbcbbbbc,0xba83ba5e,0xb334b414,
0x383d3872,0xbbe4bbd9,0xbac9baa7,0xb147b23e,0x37a13807,0xbbf5bbed,0xbb08bae9,0xaeaab04e,0x36c13732,0xbbfebbfa,0xbb41bb25,0xa97facb5,0x35da364e,0xbc00bc00,0xbb72bb5a,0x24b6a248,
0x34ed3564,0xbbf9bbfe,0xbb9dbb88,0x2d1a2a48,0x33f73475,0xbbecbbf4,0xbbc0bbaf,0x30802f0e,0x320d3303,0xbbd6bbe2,0xbbdbbbce,0x326f3179,0x301d3115,0xbbb9bbc9,0xbbefbbe6,0x342c3365,
0x2c512e46,0xbb95bba8,0xbbfbbbf6,0x351d34a5,0x1e4828b6,0xbb69bb80,0xbc00bbff,0x36083593,0xab11a648,0xbb36bb50,0xbbfdbbff,0x36ee367c,0xaf72ad7e,0xbafcbb1a,0xbbf2bbf8,0x37cd375e,
0xb1aab0b2,0xbabcbadd,0xbbe0bbea,0x3852381d,0xb396b2a1,0xba74ba99,0xbbc6bbd4,0x38ba3887,0xb4bdb444,0xba27ba4f,0xbba4bbb6,0x391d38ec,0xb5abb534,0xb9d4b9fe,0xbb7bbb91,0x397b394d,
0x3bff3c00,0xb9dcb9a8,0xa8b60000,0xb972b9a8,0x3bf43bfa,0xba3fba0f,0xaf0eacb5,0xb900b93a,0x3bdd3bea,0xba99ba6d,0xb1dbb0b2,0xb887b8c4,0x3bbc3bce,0xbae9bac2,0xb414b303,0xb807b848,
0x3b913ba8,0xbb30bb0e,0xb534b4a5,0xb705b78b,0x3b5a3b77,0xbb6ebb50,0xb64eb5c2,0xb5f1b67c,0x3b1a3b3b,0xbba0bb88,0xb75eb6d7,0xb4d5b564,0x3ad03af6,0xbbc9bbb6,0xb832b7e3,0xb365b444,
0x3a7c3aa7,0xbbe6bbd9,0xb8b0b872,0xb115b23e,0x3a1f3a4f,0xbbf8bbf1,0xb927b8ec,0xad7eafd6,0x39ba39ed,0xbc00bbfe,0xb996b95f,0xa248aa48,0x394d3984,0xbbfcbbff,0xb9feb9cb,0x2bd92648,
0x38d83913,0xbbedbbf6,0xba5eba2f,0x304e2e46,0x385d389b,0xbbd4bbe2,0xbab5ba8a,0x32a13179,0x37b7381d,0xbbafbbc3,0xbb02badd,0x347533c6,0x36aa3732,0xbb80bb99,0xbb46bb25,0x35933505,
0x3593361f,0xbb46bb64,0xbb80bb64,0x36aa361f,0x34753505,0xbb02bb25,0xbbafbb99,0x37b73732,0x32a133c6,0xbab5badd,0xbbd4bbc3,0x385d381d,0x304e3179,0xba5eba8a,0xbbedbbe2,0x38d8389b,
0x2bd92e46,0xb9feba2f,0xbbfcbbf6,0x394d3913,0xa2482648,0xb996b9cb,0xbc00bbff,0x39ba3984,0xad7eaa48,0xb927b95f,0xbbf8bbfe,0x3a1f39ed,0xb115afd6,0xb8b0b8ec,0xbbe6bbf1,0x3a7c3a4f,
0xb365b23e,0xb832b872,0xbbc9bbd9,0x3ad03aa7,0xb4d5b444,0xb75eb7e3,0xbba0bbb6,0x3b1a3af6,0xb5f1b564,0xb64eb6d7,0xbb6ebb88,0x3b5a3b3b,0xb705b67c,0xb534b5c2,0xbb30bb50,0x3b913b77,
0xb807b78b,0xb414b4a5,0xbae9bb0e,0x3bbc3ba8,0xb887b848,0xb1dbb303,0xba99bac2,0x3bdd3bce,0xb900b8c4,0xaf0eb0b2,0xba3fba6d,0x3bf43bea,0xb972b93a,0xa8b6acb5,0xb9dcba0f,0x3bff3bfa,
0x3bfe3c00,0xbb84bb64,0xa97f0000,0xb57cb61f,0x3bef3bf8,0xbbb9bba0,0xb01dad7e,0xb42cb4d5,0x3bd13be2,0xbbe0bbce,0xb2d2b179,0xb1aab303,0x3ba43bbc,0xbbf7bbed,0xb4bdb414,0xade2b04e,
0x3b693b88,0xbc00bbfe,0xb608b564,0x9e48aa48,0x3b203b46,0xbbf9bbff,0xb748b6aa,0x2d1a28b6,0x3ac93af6,0xbbe4bbf1,0xb83db7e3,0x31472fd6,0x3a653a99,0xbbc0bbd4,0xb8ceb887,0x33f732a1,
0x39f63a2f,0xbb8cbba8,0xb956b913,0x354c34a5,0x397b39ba,0xbb4bbb6e,0xb9d4b996,0x369335f1,0x38f6393a,0xbafcbb25,0xba47ba0f,0x37cd3732,0x386738b0,0xbaa0bad0,0xbaaeba7c,0x387c3832,
0x37a1381d,0xba37ba6d,0xbb08badd,0x390938c4,0x36653705,0xb9c3b9fe,0xbb55bb30,0x398d394d,0x351d35c2,0xb943b984,0xbb95bb77,0x3a0739cb,0x33963475,0xb8bab900,0xbbc6bbaf,0x3a743a3f,
0x30e4323e,0xb828b872,0xbbe8bbd9,0x3ad63aa7,0x2c512f0e,0xb71bb7b7,0xbbfbbbf4,0x3b2b3b02,0xa4b62648,0xb5dab67c,0xbc00bbff,0x3b723b50,0xaeaaabd9,0xb48db534,0xbbf5bbfc,0x3bab3b91,
0xb20db0b2,0xb26fb3c6,0xbbdbbbea,0x3bd63bc3,0xb45db365,0xaf72b115,0xbbb2bbc9,0x3bf23be6,0xb5abb505,0xa7daacb5,0xbb7bbb99,0x3bff3bfa,0xb6eeb64e,0x2b112248,0xbb36bb5a,0x3bfd3c00,
0xb812b78b,0x30802e46,0xbae3bb0e,0x3bec3bf6,0xb8a6b85d,0x333431db,0xba83bab5,0x3bcb3bdd,0xb930b8ec,0x34ed3444,0xba17ba4f,0x3b9d3bb6,0xb9b1b972,0x36373593,0xb99fb9dc,0x3b5f3b80,
0xba27b9ed,0x377536d7,0xb91db95f,0x3b143b3b,0xba92ba5e,0x38523807,0xb891b8d8,0x3abc3ae9,0xbaf0bac2,0x38e2389b,0xb7f9b848,0x3a563a8a,0xbb41bb1a,0x39693927,0xb6c1b75e,0x39e53a1f
};
#define SENT 0xFFFFFFFFu
#define SPIN_MAX (1 << 20)

__device__ __forceinline__ __half2 H(u32 v) { return *reinterpret_cast<__half2*>(&v); }
__device__ __forceinline__ u32 U(__half2 v) { return *reinterpret_cast<u32*>(&v); }
__device__ __forceinline__ u32 hadd(u32 a, u32 b) { return U(__hadd2(H(a), H(b))); }
__device__ __forceinline__ u32 hsub(u32 a, u32 b) { return U(__hsub2(H(a), H(b))); }
__device__ __forceinline__ u32 hmul(u32 a, u32 b) { return U(__hmul2(H(a), H(b))); }
__device__ __forceinline__ u32 hfma(u32 a, u32 b, u32 c) { return U(__hfma2(H(a), H(b), H(c))); }
__device__ __forceinline__ u32 hfnma(u32 a, u32 b, u32 c) { return U(__hfma2(__hneg2(H(a)), H(b), H(c))); }
__device__ __forceinline__ u32 pkh(float lo, float hi) { return U(__floats2half2_rn(lo, hi)); }
__device__ __forceinline__ u32 pkb(float lo, float hi) { __nv_bfloat162 v = __floats2bfloat162_rn(lo, hi); return *reinterpret_cast<u32*>(&v); }
__device__ __forceinline__ float blo(u32 v) { return __uint_as_float(v << 16); }
__device__ __forceinline__ float bhi(u32 v) { return __uint_as_float(v & 0xFFFF0000u); }
__device__ __forceinline__ float rbf(float v) { return __bfloat162float(__float2bfloat16_rn(v)); }
__device__ __forceinline__ u32 badd(u32 a, u32 b) { __nv_bfloat162 v = __hadd2(*reinterpret_cast<__nv_bfloat162*>(&a), *reinterpret_cast<__nv_bfloat162*>(&b)); return *reinterpret_cast<u32*>(&v); }
__device__ __forceinline__ u32 bsub(u32 a, u32 b) { __nv_bfloat162 v = __hsub2(*reinterpret_cast<__nv_bfloat162*>(&a), *reinterpret_cast<__nv_bfloat162*>(&b)); return *reinterpret_cast<u32*>(&v); }
__device__ __forceinline__ u32 bmul(u32 a, u32 b) { u32 d; asm("mul.rn.bf16x2 %0,%1,%2;" : "=r"(d) : "r"(a), "r"(b)); return d; }
__device__ __forceinline__ u32 bfma(u32 a, u32 b, u32 c) { u32 d; asm("fma.rn.bf16x2 %0,%1,%2,%3;" : "=r"(d) : "r"(a), "r"(b), "r"(c)); return d; }
__device__ __forceinline__ void cmul(u32& r, u32& m, u32 c, u32 s) { u32 t = hfnma(m, s, hmul(r, c)); m = hfma(r, s, hmul(m, c)); r = t; }
__device__ __forceinline__ void cmulc(u32& r, u32& m, u32 c, u32 s) { u32 t = hfma(m, s, hmul(r, c)); m = hfnma(r, s, hmul(m, c)); r = t; }
__device__ __forceinline__ void tw2(int n0, int n1, int den, float sc, u32& c, u32& s) {
    n0 = ((n0 + den / 2) & (den - 1)) - den / 2;
    n1 = ((n1 + den / 2) & (den - 1)) - den / 2;
    float k = -6.283185307179586f / den, s0, c0, s1, c1;
    __sincosf(n0 * k, &s0, &c0);
    __sincosf(n1 * k, &s1, &c1);
    c = pkh(c0 * sc, c1 * sc);
    s = pkh(s0 * sc, s1 * sc);
}
__device__ __forceinline__ void mma0(u32& d0, u32& d1, u32 a0, u32 a1, u32 a2, u32 a3, u32 b0, u32 b1) {
    asm("mma.sync.aligned.m16n8k16.row.col.f16.f16.f16.f16 {%0,%1},{%2,%3,%4,%5},{%6,%7},{%8,%8};"
        : "=r"(d0), "=r"(d1) : "r"(a0), "r"(a1), "r"(a2), "r"(a3), "r"(b0), "r"(b1), "r"(0));
}
__device__ __forceinline__ void mma1(u32& d0, u32& d1, u32 a0, u32 a1, u32 a2, u32 a3, u32 b0, u32 b1) {
    asm("mma.sync.aligned.m16n8k16.row.col.f16.f16.f16.f16 {%0,%1},{%2,%3,%4,%5},{%6,%7},{%0,%1};"
        : "+r"(d0), "+r"(d1) : "r"(a0), "r"(a1), "r"(a2), "r"(a3), "r"(b0), "r"(b1));
}
__device__ __forceinline__ void mmab(float* c, u32 a0, u32 a1, u32 a2, u32 a3, u32 b0, u32 b1) {
    asm("mma.sync.aligned.m16n8k16.row.col.f32.bf16.bf16.f32 {%0,%1,%2,%3},{%4,%5,%6,%7},{%8,%9},{%0,%1,%2,%3};"
        : "+f"(c[0]), "+f"(c[1]), "+f"(c[2]), "+f"(c[3]) : "r"(a0), "r"(a1), "r"(a2), "r"(a3), "r"(b0), "r"(b1));
}
__device__ __forceinline__ void ldsm(u32& a, u32& b, u32& c, u32& d, u32 addr) {
    asm volatile("ldmatrix.sync.aligned.m8n8.x4.shared.b16 {%0,%1,%2,%3},[%4];" : "=r"(a), "=r"(b), "=r"(c), "=r"(d) : "r"(addr) : "memory");
}
__device__ __forceinline__ void ldsmt(u32& a, u32& b, u32& c, u32& d, u32 addr) {
    asm volatile("ldmatrix.sync.aligned.m8n8.x4.trans.shared.b16 {%0,%1,%2,%3},[%4];" : "=r"(a), "=r"(b), "=r"(c), "=r"(d) : "r"(addr) : "memory");
}
__device__ __forceinline__ void stsm(u32 addr, u32 a, u32 b, u32 c, u32 d) {
    asm volatile("stmatrix.sync.aligned.m8n8.x4.shared.b16 [%0],{%1,%2,%3,%4};" :: "r"(addr), "r"(a), "r"(b), "r"(c), "r"(d) : "memory");
}
__device__ __forceinline__ void lds128(u32* v, u32 addr) {
    asm volatile("ld.shared.v4.u32 {%0,%1,%2,%3},[%4];" : "=r"(v[0]), "=r"(v[1]), "=r"(v[2]), "=r"(v[3]) : "r"(addr) : "memory");
}
__device__ __forceinline__ void sts128(u32 addr, u32 a, u32 b, u32 c, u32 d) {
    asm volatile("st.shared.v4.u32 [%0],{%1,%2,%3,%4};" :: "r"(addr), "r"(a), "r"(b), "r"(c), "r"(d) : "memory");
}
__device__ __forceinline__ void lds64(u32* v, u32 addr) { asm volatile("ld.shared.v2.u32 {%0,%1},[%2];" : "=r"(v[0]), "=r"(v[1]) : "r"(addr) : "memory"); }
__device__ __forceinline__ void sts64(u32 addr, u32 a, u32 b) { asm volatile("st.shared.v2.u32 [%0],{%1,%2};" :: "r"(addr), "r"(a), "r"(b) : "memory"); }
__device__ __forceinline__ u32 lds16(u32 addr) { unsigned short v; asm volatile("ld.shared.u16 %0,[%1];" : "=h"(v) : "r"(addr) : "memory"); return v; }
__device__ __forceinline__ void sts16(u32 addr, u32 v) { asm volatile("st.shared.u16 [%0],%1;" :: "r"(addr), "h"((unsigned short)v) : "memory"); }
__device__ __forceinline__ u32 lds32(u32 addr) { u32 v; asm volatile("ld.shared.u32 %0,[%1];" : "=r"(v) : "r"(addr) : "memory"); return v; }
__device__ __forceinline__ void sts32(u32 addr, u32 v) { asm volatile("st.shared.u32 [%0],%1;" :: "r"(addr), "r"(v) : "memory"); }
__device__ __forceinline__ void mb_wait(u32 mb, u32 par) {
    u32 ok; int it = 0;
    do {
        asm volatile("{.reg .pred p; mbarrier.try_wait.parity.shared::cta.b64 p,[%1],%2,%3; selp.u32 %0,1,0,p;}" : "=r"(ok) : "r"(mb), "r"(par), "r"(SUSP_NS) : "memory");
        if (++it > SPIN_MAX) break;
    } while (!ok);
}
__device__ __forceinline__ void mb_expect(u32 mb, u32 bytes) { asm volatile("mbarrier.arrive.expect_tx.shared::cta.b64 _,[%0],%1;" :: "r"(mb), "r"(bytes) : "memory"); }
__device__ __forceinline__ void mb_arrive(u32 mb) { asm volatile("mbarrier.arrive.shared::cta.b64 _,[%0];" :: "r"(mb) : "memory"); }
__device__ __forceinline__ void g2s(u32 dst, const void* src, u32 bytes, u32 mb) {
    asm volatile("cp.async.bulk.shared::cluster.global.mbarrier::complete_tx::bytes [%0],[%1],%2,[%3];" :: "r"(dst), "l"(src), "r"(bytes), "r"(mb) : "memory");
}
__device__ __forceinline__ u64 pol_stream() { u64 p; asm("createpolicy.fractional.L2::evict_first.b64 %0,1.0;" : "=l"(p)); return p; }
__device__ __forceinline__ void g2sx(u32 dst, const void* src, u32 bytes, u32 mb) {
    asm volatile("cp.async.bulk.shared::cluster.global.mbarrier::complete_tx::bytes.L2::cache_hint [%0],[%1],%2,[%3],%4;" :: "r"(dst), "l"(src), "r"(bytes), "r"(mb), "l"(pol_stream()) : "memory");
}
__device__ __forceinline__ void g2s2d(u32 dst, const CUtensorMap* tm, int c0, int c1, u32 mb) {
    asm volatile("cp.async.bulk.tensor.2d.shared::cluster.global.mbarrier::complete_tx::bytes.L2::cache_hint [%0],[%1,{%2,%3}],[%4],%5;" :: "r"(dst), "l"(tm), "r"(c0), "r"(c1), "r"(mb), "l"(pol_stream()) : "memory");
}
__device__ __forceinline__ void g2s3d(u32 dst, const CUtensorMap* tm, int c0, int c1, int c2, u32 mb) {
    asm volatile("cp.async.bulk.tensor.3d.shared::cluster.global.mbarrier::complete_tx::bytes.L2::cache_hint [%0],[%1,{%2,%3,%4}],[%5],%6;" :: "r"(dst), "l"(tm), "r"(c0), "r"(c1), "r"(c2), "r"(mb), "l"(pol_stream()) : "memory");
}
__device__ __forceinline__ void s2g(void* dst, u32 src, u32 bytes) {
    asm volatile("cp.async.bulk.global.shared::cta.bulk_group [%0],[%1],%2;" :: "l"(dst), "r"(src), "r"(bytes) : "memory");
}
__device__ __forceinline__ void s2g2d(const CUtensorMap* tm, int c0, int c1, u32 src) {
    asm volatile("cp.async.bulk.tensor.2d.global.shared::cta.bulk_group [%0,{%1,%2}],[%3];" :: "l"(tm), "r"(c0), "r"(c1), "r"(src) : "memory");
}
__device__ __forceinline__ void s2g3d(const CUtensorMap* tm, int c0, int c1, int c2, u32 src) {
    asm volatile("cp.async.bulk.tensor.3d.global.shared::cta.bulk_group [%0,{%1,%2,%3}],[%4];" :: "l"(tm), "r"(c0), "r"(c1), "r"(c2), "r"(src) : "memory");
}
__device__ __forceinline__ void pf_map(const CUtensorMap* tm) { asm volatile("prefetch.tensormap [%0];" :: "l"(tm) : "memory"); }
__device__ __forceinline__ void ldt(u32 tb, int i, u32& a, u32& b, u32& c, u32& d) { u32 v[4]; lds128(v, tb + i * 512 + (i >= 12 ? SM_TAB2 - SM_TAB - 6144 : 0)); a = v[0]; b = v[1]; c = v[2]; d = v[3]; }
__device__ __forceinline__ void s2g_wait() { asm volatile("cp.async.bulk.commit_group;\n cp.async.bulk.wait_group 0;" ::: "memory"); }
__device__ __forceinline__ void fence_async() { asm volatile("fence.proxy.async.shared::cta;" ::: "memory"); }
__device__ __forceinline__ void bar_c() { asm volatile("bar.sync 1, 256;" ::: "memory"); }
__device__ __forceinline__ void red_add(u32* p) {
    asm volatile("red.relaxed.gpu.global.add.u32 [%0],1;" :: "l"(p) : "memory");
}
__device__ __forceinline__ void poll32(const u32* p, u32 target) {
    u32 v; int it = 0;
    do { asm volatile("ld.relaxed.gpu.global.u32 %0,[%1];" : "=r"(v) : "l"(p) : "memory"); if (++it > SPIN_MAX) break; } while ((int)(v - target) < 0);
}
__device__ __forceinline__ void max_arrive(u64* p, u32 key) {
    asm volatile("red.relaxed.gpu.global.max.u32 [%0],%1;\n red.relaxed.gpu.global.add.u64 [%0],%2;" :: "l"(p), "r"(key), "l"(1ull << 32) : "memory");
}
__device__ __forceinline__ u32 epoch_target(const u32* p) {
    u32 v;
    asm volatile("ld.relaxed.gpu.global.u32 %0,[%1];" : "=r"(v) : "l"(p) : "memory");
    return (v & ~(u32)(NCTA - 1)) + NCTA;
}
__device__ __forceinline__ u32 max_poll(const u64* p, u32 target) {
    u64 v; int it = 0;
    do { asm volatile("ld.relaxed.gpu.global.u64 %0,[%1];" : "=l"(v) : "l"(p) : "memory"); if (++it > SPIN_MAX) break; } while ((int)((u32)(v >> 32) - target) < 0);
    return (u32)v;
}
__device__ __forceinline__ void dft8(u32 (&r)[8][2], u32 (&m)[8][2], int h) {
    const u32 C = 0x39A839A8u;
    u32 s0r = hadd(r[0][h], r[4][h]), d0r = hsub(r[0][h], r[4][h]), s0i = hadd(m[0][h], m[4][h]), d0i = hsub(m[0][h], m[4][h]);
    u32 s1r = hadd(r[1][h], r[5][h]), d1r = hsub(r[1][h], r[5][h]), s1i = hadd(m[1][h], m[5][h]), d1i = hsub(m[1][h], m[5][h]);
    u32 s2r = hadd(r[2][h], r[6][h]), d2r = hsub(r[2][h], r[6][h]), s2i = hadd(m[2][h], m[6][h]), d2i = hsub(m[2][h], m[6][h]);
    u32 s3r = hadd(r[3][h], r[7][h]), d3r = hsub(r[3][h], r[7][h]), s3i = hadd(m[3][h], m[7][h]), d3i = hsub(m[3][h], m[7][h]);
    u32 e0r = hadd(s0r, s2r), e0i = hadd(s0i, s2i), e1r = hsub(s0r, s2r), e1i = hsub(s0i, s2i);
    u32 e2r = hadd(s1r, s3r), e2i = hadd(s1i, s3i), e3r = hsub(s1r, s3r), e3i = hsub(s1i, s3i);
    r[0][h] = hadd(e0r, e2r); m[0][h] = hadd(e0i, e2i); r[4][h] = hsub(e0r, e2r); m[4][h] = hsub(e0i, e2i);
    r[2][h] = hadd(e1r, e3i); m[2][h] = hsub(e1i, e3r); r[6][h] = hsub(e1r, e3i); m[6][h] = hadd(e1i, e3r);
    u32 o0r = hadd(d0r, d2i), o0i = hsub(d0i, d2r), o1r = hsub(d0r, d2i), o1i = hadd(d0i, d2r);
    u32 ar = hadd(d1r, d1i), ai = hsub(d1i, d1r), br = hsub(d3i, d3r), bn = hadd(d3r, d3i);
    u32 pr = hadd(ar, br), pi = hsub(ai, bn), qr = hsub(ar, br), qi = hadd(ai, bn);
    r[1][h] = hfma(pr, C, o0r); m[1][h] = hfma(pi, C, o0i); r[5][h] = hfnma(pr, C, o0r); m[5][h] = hfnma(pi, C, o0i);
    r[3][h] = hfma(qi, C, o1r); m[3][h] = hfnma(qr, C, o1i); r[7][h] = hfnma(qi, C, o1r); m[7][h] = hfma(qr, C, o1i);
}
__device__ __forceinline__ void row_stats2(const u32 (&va)[8][2], const u32 (&vb)[8][2], int g, int t4, float (&mean)[2], float (&rstd)[2], float* dot = nullptr) {
    float c[4][4];
#pragma unroll
    for (int i = 0; i < 4; i++) c[i][0] = c[i][1] = c[i][2] = c[i][3] = 0.f;
    const u32 one = 0x3F803F80u;
#pragma unroll
    for (int t = 0; t < 8; t += 2) {
        mmab(c[0], va[t][0], one, va[t][1], one, va[t][0], va[t][1]);
        mmab(c[1], vb[t][0], one, vb[t][1], one, vb[t][0], vb[t][1]);
        mmab(c[2], va[t + 1][0], one, va[t + 1][1], one, va[t + 1][0], va[t + 1][1]);
        mmab(c[3], vb[t + 1][0], one, vb[t + 1][1], one, vb[t + 1][0], vb[t + 1][1]);
    }
    const bool dg = (t4 == (g >> 1));
    float q[2], s[2];
#pragma unroll
    for (int r = 0; r < 2; r++) {
        q[r] = dg ? ((g & 1) ? c[r][1] + c[r + 2][1] : c[r][0] + c[r + 2][0]) : 0.f;
        s[r] = (c[r][2] + c[r][3]) + (c[r + 2][2] + c[r + 2][3]);
    }
#pragma unroll
    for (int o = 1; o < 32; o <<= 1) {
        q[0] += __shfl_xor_sync(~0u, q[0], o); q[1] += __shfl_xor_sync(~0u, q[1], o);
        if (dot) { dot[0] += __shfl_xor_sync(~0u, dot[0], o); dot[1] += __shfl_xor_sync(~0u, dot[1], o); }
        if (o < 4) { s[0] += __shfl_xor_sync(~0u, s[0], o); s[1] += __shfl_xor_sync(~0u, s[1], o); }
    }
#pragma unroll
    for (int r = 0; r < 2; r++) {
        float mu = s[r] * (1.f / 1024.f);
        float var = fmaxf(q[r] * (1.f / 1024.f) - mu * mu, 0.f), sd, rc;
        mean[r] = rbf(mu);
        asm("sqrt.approx.f32 %0,%1;" : "=f"(sd) : "f"(rbf(rbf(var) + 1e-5f)));
        asm("rcp.approx.f32 %0,%1;" : "=f"(rc) : "f"(rbf(sd)));
        rstd[r] = rc;
    }
}
__device__ __forceinline__ u32 gswz(int G) { return (u32)(G ^ (((G >> 4) & 3) << 1)) * 16u; }

struct P2C { u32 Fr[4], Fi[4], Fn[4], T1c[2], T1s[2], Bc[2], Bs[2], f8r, f8i, f8n; };
__device__ __forceinline__ void col_fwd(const P2C& k, u32 br0, u32 br1, u32 bi0, u32 bi1, const u32* wr, const u32* wi, u32* zr, u32* zi) {
    u32 ur0, ur1, ui0, ui1, vr[2], vi[2];
    mma0(ur0, ur1, k.Fr[0], k.Fr[1], k.Fr[2], k.Fr[3], br0, br1);
    mma0(ui0, ui1, k.Fi[0], k.Fi[1], k.Fi[2], k.Fi[3], br0, br1);
    mma1(ur0, ur1, k.Fn[0], k.Fn[1], k.Fn[2], k.Fn[3], bi0, bi1);
    mma1(ui0, ui1, k.Fr[0], k.Fr[1], k.Fr[2], k.Fr[3], bi0, bi1);
    cmul(ur0, ui0, k.T1c[0], k.T1s[0]);
    cmul(ur1, ui1, k.T1c[1], k.T1s[1]);
    mma0(vr[0], vr[1], ur0, ur1, ui0, ui1, k.f8r, k.f8n);
    mma0(vi[0], vi[1], ur0, ur1, ui0, ui1, k.f8i, k.f8r);
#pragma unroll
    for (int h = 0; h < 2; h++) {
        cmul(vr[h], vi[h], wr[h], wi[h]);
        mma0(zr[h], zi[h], k.f8r, k.f8n, k.f8i, k.f8r, vr[h], vi[h]);
        cmulc(zr[h], zi[h], k.Bc[h], k.Bs[h]);
    }
}
__device__ __forceinline__ void inv16(const u32* Fr, const u32* Fi, const u32* Fn, u32* zr, u32* zi) {
    u32 o0, o1, p0, p1;
    mma0(o0, o1, Fr[0], Fr[1], Fr[2], Fr[3], zr[0], zr[1]);
    mma0(p0, p1, Fn[0], Fn[1], Fn[2], Fn[3], zr[0], zr[1]);
    mma1(o0, o1, Fi[0], Fi[1], Fi[2], Fi[3], zi[0], zi[1]);
    mma1(p0, p1, Fr[0], Fr[1], Fr[2], Fr[3], zi[0], zi[1]);
    zr[0] = o0; zr[1] = o1; zi[0] = p0; zi[1] = p1;
}

__global__ void __launch_bounds__(NTHR, 1)
fused_kernel(const __nv_bfloat16* __restrict__ x,
             const __nv_bfloat16* __restrict__ rw,
             __nv_bfloat16* __restrict__ out, Scratch* __restrict__ gs, const uint4* __restrict__ tab,
             const __grid_constant__ CUtensorMap tm_s1, const __grid_constant__ CUtensorMap tm_s2,
             const __grid_constant__ CUtensorMap tm_n1, const __grid_constant__ CUtensorMap tm_n2, const __grid_constant__ CUtensorMap tm_o,
             const __grid_constant__ CUtensorMap tm_wr, const __grid_constant__ CUtensorMap tm_wi,
             const __grid_constant__ CUtensorMap tm_g, const __grid_constant__ CUtensorMap tm_u, const __grid_constant__ CUtensorMap tm_d) {
    extern __shared__ __align__(1024) unsigned char smem[];
    const u32 sb = (u32)__cvta_generic_to_shared(smem);
    const u32 mbb = sb + SM_MISC;
    const int tid = threadIdx.x, lane = tid & 31, w = tid >> 5, b = blockIdx.x;
    const int g = lane >> 2, t4 = lane & 3;
    const int k1a = b >> 3, cg = b & 7;
    const long long t00 = clock64();
#define MB(i) (mbb + 8 * (i))
#define FILL_GU(q, mb) g2s2d(sb + SM_GU + (((q) >> 2) & 1) * 65536 + ((q) >> 3) * 16384 + ((q) & 3) * 4096, ((q) & 4) ? &tm_u : &tm_g, b * 32, ((q) >> 3) * 256 + ((q) & 3) * 64, mb)
    if (w >= 8) {
        asm volatile("setmaxnreg.dec.sync.aligned.u32 %0;" :: "n"(RHELP));
        if (w == 8) {
            if (lane >= 8 && lane < NMB) {
                int cnt = (lane == MB_INIT || lane == MB_AM) ? 32 : (lane == MB_GU) ? 2 : (lane == MB_D1F || (lane >= MB_ST1 && lane < MB_ST2 + 2) || lane >= MB_WC) ? 8 : 1;
                asm volatile("mbarrier.init.shared::cta.b64 [%0],%1;" :: "r"(MB(lane)), "r"(cnt) : "memory");
            }
            if (lane < 8) asm volatile("mbarrier.init.shared::cta.b64 [%0],1;" :: "r"(MB(MB_F0 + lane)) : "memory");
            fence_async();
            __syncwarp();
            asm volatile("bar.arrive 2, 288;" ::: "memory");
        }
        asm volatile("bar.sync 3, 128;" ::: "memory");
        if (w == 11) {
            uint4 sv = make_uint4(SENT, SENT, SENT, SENT);
            for (int i = lane; i < 256; i += 32) {
                reinterpret_cast<uint4*>(gs->cand + b * 1024)[i] = sv;
                if (i < NFFN * 2) reinterpret_cast<uint4*>(gs->part + b * NFFN * 8)[i] = sv;
            }
            if (b == 0) reinterpret_cast<uint4*>(gs->cnt2)[lane] = make_uint4(0, 0, 0, 0);
            __threadfence();
            mb_arrive(MB(MB_INIT));
            if (lane == 0) {
                mb_expect(MB(MB_IN2), 16384); mb_expect(MB(MB_IN2 + 1), cg == 7 ? 20480 : 16384);
                mb_expect(MB(MB_IN3), 16384); mb_expect(MB(MB_IN3 + 1), 16896);
                mb_wait(MB(MB_TGT), 0);
                mb_wait(MB(MB_ST1 + 1), 0);
                for (int hf = 0; hf < 2; hf++) {
                    poll32(&gs->cnt1[32 * hf], lds32(mbb + MS_WIN + 8 + 4 * hf));
                    for (int i = 0; i < 2; i++) g2s(sb + SM_E + hf * 16384 + i * 8192, gs->s1 + (hf * 128 + b) * 1024 + i * 512, 8192, MB(MB_IN2 + hf));
                }
                if (cg == 7) { mb_wait(MB(MB_WC), 0); g2s(sb + SM_D0, gs->n1 + k1a * 256, 4096, MB(MB_IN2 + 1)); }
                mb_wait(MB(MB_ST2), 0);
                for (int hf = 0; hf < 2; hf++) {
                    poll32(&gs->cnt2[32 * hf], NCTA);
                    if (hf) { g2s(mbb + MS_PART, gs->n2 + b * 32, 512, MB(MB_IN3 + 1)); }
                    for (int i = 0; i < 2; i++) g2s(sb + SM_D1 + hf * 16384 + i * 8192, gs->s2 + (hf * 128 + b) * 1024 + i * 512, 8192, MB(MB_IN3 + hf));
                }
            }
        } else if (tid == 320) {
            if (b < NFFN) {
                while (clock64() < t00 + FILL_T0) __nanosleep(40);
                int n = 0;
                for (; n < 32; n++) {
                    if (n >= FILL_W) mb_wait(MB(MB_F0 + (n % FILL_W)), ((n / FILL_W) - 1) & 1);
                    u32 ok;
                    asm volatile("{.reg .pred p; mbarrier.test_wait.parity.shared::cta.b64 p,[%1],0; selp.u32 %0,1,0,p;}" : "=r"(ok) : "r"(MB(MB_D1F)) : "memory");
                    if (ok) break;
                    if (n == 24) mb_wait(MB(MB_WC), 0);
                    mb_expect(MB(MB_F0 + (n % FILL_W)), 4096);
                    FILL_GU(n, MB(MB_F0 + (n % FILL_W)));
                }
                mb_wait(MB(MB_D1F), 0);
                mb_expect(MB(MB_GU), (32 - n) * 4096);
                mb_expect(MB(MB_DN), 65536);
                for (int q = n; q < 32; q++) FILL_GU(q, MB(MB_GU));
                for (int i = 0; i < DN_EARLY; i++) g2s3d(sb + SM_D0 + i * 16384, &tm_d, 0, b * 32, 4 * i, MB(MB_DN));
                for (int q = (n > FILL_W ? n - FILL_W : 0); q < n; q++) mb_wait(MB(MB_F0 + (q % FILL_W)), (q / FILL_W) & 1);
                mb_arrive(MB(MB_GU));
                if (DN_EARLY < 4) mb_wait(MB(MB_GU), 0);
                for (int i = DN_EARLY; i < 4; i++) g2s3d(sb + SM_D0 + i * 16384, &tm_d, 0, b * 32, 4 * i, MB(MB_DN));
            }
        } else if (w == 9) {
            u32 win = 0;
            if (lane == 0) {
            const u32 tw = epoch_target(reinterpret_cast<const u32*>(gs->wmax) + 1);
            pf_map(&tm_s1); pf_map(&tm_n1); pf_map(&tm_s2); pf_map(&tm_n2); pf_map(&tm_o);
            sts32(mbb + MS_WIN + 8, epoch_target(&gs->cnt1[0]));
            sts32(mbb + MS_WIN + 12, epoch_target(&gs->cnt1[32]));
            mb_arrive(MB(MB_TGT));
            mb_wait(MB(MB_ST1), 0);
            s2g3d(&tm_s1, b * 64, 0, 0, sb + SM_D1);
            asm volatile("cp.async.bulk.commit_group;" ::: "memory");
            mb_wait(MB(MB_ST1 + 1), 0);
            s2g3d(&tm_s1, b * 64, 0, 16, sb + SM_D1 + 16384);
            s2g2d(&tm_n1, b * 16, 0, mbb + MS_PART);
            asm volatile("cp.async.bulk.commit_group;\n cp.async.bulk.wait_group 1;" ::: "memory");
            red_add(&gs->cnt1[0]);
            asm volatile("cp.async.bulk.wait_group 0;" ::: "memory");
            red_add(&gs->cnt1[32]);
            {
                mb_wait(MB(MB_INIT), 0);
                mb_wait(MB(MB_WC), 0);
                u32 k4[4], k5[4];
                lds128(k4, mbb + MS_EXP); lds128(k5, mbb + MS_EXP + 16);
                max_arrive(gs->wmax, max(max(max(k4[0], k4[1]), max(k4[2], k4[3])), max(max(k5[0], k5[1]), max(k5[2], k5[3]))));
                sts32(mbb + MS_WIN + 4, max_poll(gs->wmax, tw));
                mb_arrive(MB(MB_SC));
            }
            mb_wait(MB(MB_ST2), 0);
            s2g2d(&tm_s2, (cg * 16 + k1a) * 64, 0, sb + SM_D1);
            s2g_wait();
            red_add(&gs->cnt2[0]);
            mb_wait(MB(MB_ST2 + 1), 0);
            s2g2d(&tm_s2, (cg * 16 + k1a) * 64, 128, sb + SM_D1 + 16384);
            if (cg == 7) s2g2d(&tm_n2, k1a * 16, 0, sb + SM_D0 + 4096);
            s2g_wait();
            red_add(&gs->cnt2[32]);
            mb_wait(MB(MB_KEY), 0);
            u32 k4[4], k5[4];
            lds128(k4, mbb + MS_KEY); lds128(k5, mbb + MS_KEY + 16);
            max_arrive(gs->amax, max(max(max(k4[0], k4[1]), max(k4[2], k4[3])), max(max(k5[0], k5[1]), max(k5[2], k5[3]))));
            }
            __syncwarp();
            u32 hv, lv;
            int idx;
            {
                u32 v[4][4];
                int it = 0;
                bool ok;
                do {
                    const u32* cp = gs->cand + ((2047 - (int)(win & 0xFFFFu)) & 127) * 1024;
                    u64 am;
                    asm volatile("ld.relaxed.gpu.global.u64 %0,[%1];" : "=l"(am) : "l"(gs->amax) : "memory");
                    ok = false;
                    if (win) {
                        asm volatile("ld.relaxed.gpu.global.u32 %0,[%1];" : "=r"(hv) : "l"(cp + 512 + 4 * b + t4) : "memory");
                        ok = hv != SENT;
#pragma unroll
                        for (int i = 0; i < 4; i++) {
                            asm volatile("ld.relaxed.gpu.global.v4.u32 {%0,%1,%2,%3},[%4];" : "=r"(v[i][0]), "=r"(v[i][1]), "=r"(v[i][2]), "=r"(v[i][3]) : "l"(cp + 128 * i + 4 * lane) : "memory");
                            ok = ok && v[i][0] != SENT && v[i][1] != SENT && v[i][2] != SENT && v[i][3] != SENT;
                        }
                    }
                    ok = ok && (u32)am == win && (u32)(am >> 32) >= NCTA;
                    win = ((u32)(am >> 32) >= SPEC_MIN) ? (u32)am : 0u;
                    win = __shfl_sync(~0u, win, 0);
                    if (++it > SPIN_MAX) break;
                } while (!__all_sync(~0u, ok));
                idx = 2047 - (int)(win & 0xFFFFu);
#pragma unroll
                for (int i = 0; i < 4; i++) sts128(mbb + MS_PART + 512 * i + 16 * lane, v[i][0], v[i][1], v[i][2], v[i][3]);
                mb_arrive(MB(MB_AM));
                __syncwarp();
                lv = lds32(mbb + MS_PART + 16 * b + 4 * t4);
            }
            if (lane == 0) {
                if (b == 0) *reinterpret_cast<u32*>(gs->wmax) = 0;
                mb_wait(MB(MB_OUT), 0);
                if ((idx & 127) != b) s2g3d(&tm_o, 0, 4 * b, 0, sb + SM_E);
                else for (int r = 0; r < 16; r++) if (r != (idx >> 7)) s2g(out + (size_t)(128 * r + b) * 1024, sb + SM_E + r * 2048, 2048);
                mb_wait(MB(MB_PS), 0);
                if (b < NFFN) red_add(gs->cnt3);
                poll32(gs->cnt3, NFFN);
            }
            __syncwarp();
            float s0, s1, s2, s3;
            {
                int it = 0;
                bool ok;
                do {
                    u32 a[7][4];
#pragma unroll
                    for (int i = 0; i < 7; i++)
                        asm volatile("ld.relaxed.gpu.global.v4.u32 {%0,%1,%2,%3},[%4];" : "=r"(a[i][0]), "=r"(a[i][1]), "=r"(a[i][2]), "=r"(a[i][3]) : "l"(gs->part + b * NFFN * 8 + i * 128 + lane * 4) : "memory");
                    ok = true;
                    s0 = s1 = s2 = s3 = 0.f;
#pragma unroll
                    for (int i = 0; i < 7; i++) {
                        ok = ok && a[i][0] != SENT && a[i][1] != SENT && a[i][2] != SENT && a[i][3] != SENT;
                        s0 += __uint_as_float(a[i][0]); s1 += __uint_as_float(a[i][1]); s2 += __uint_as_float(a[i][2]); s3 += __uint_as_float(a[i][3]);
                    }
                    if (++it > SPIN_MAX) break;
                } while (!__all_sync(~0u, ok));
            }
            {
                float k0 = (lane & 2) ? s2 : s0, k1 = (lane & 2) ? s3 : s1;
                k0 += __shfl_xor_sync(~0u, (lane & 2) ? s0 : s2, 2);
                k1 += __shfl_xor_sync(~0u, (lane & 2) ? s1 : s3, 2);
#pragma unroll
                for (int o = 4; o < 32; o <<= 1) { k0 += __shfl_xor_sync(~0u, k0, o); k1 += __shfl_xor_sync(~0u, k1, o); }
                const int src = ((t4 & 1) << 1) | (t4 >> 1);
                k0 = __shfl_sync(~0u, k0, src); k1 = __shfl_sync(~0u, k1, src);
                const u32 kb = win >> 16;
                const float r = blo((kb & 0x8000u) ? (kb & 0x7FFFu) : (~kb & 0xFFFFu));
                const float sg = rbf(__fdividef(1.f, 1.f + __expf(-r)));
                const u32 upd = pkb(rbf(k0) * sg, rbf(k1) * sg);
                if (lane < 4) reinterpret_cast<u32*>(out)[(size_t)idx * 512 + 4 * b + lane] = badd(hv, badd(lv, upd));
            }
            if (lane == 0) { s2g_wait(); }
        } else if (tid == 256) {
            mb_expect(MB(MB_W), 36864 + 5120 + 2048);
            g2s2d(sb + SM_W, &tm_wr, (k1a * 513 + cg * 64) & ~7, 0, MB(MB_W));
            g2s2d(sb + SM_W + 18432, &tm_wi, (k1a * 513 + cg * 64) & ~7, 0, MB(MB_W));
            g2s(sb + SM_TAB2, tab + 384, 5120, MB(MB_W));
            g2s(sb + SM_TAB2 + 5120, rw, 2048, MB(MB_W));
            pf_map(&tm_g); pf_map(&tm_u); pf_map(&tm_d);
        }
    } else {
    if (lane == 0) {
        asm volatile("mbarrier.init.shared::cta.b64 [%0],1;" :: "r"(MB(MB_X + w)) : "memory");
        if (w == 0) asm volatile("mbarrier.init.shared::cta.b64 [%0],1;" :: "r"(MB(MB_TAB)) : "memory");
        fence_async();
        if (w == 0) {
            mb_expect(MB(MB_TAB), 6144);
            g2s(sb + SM_TAB, tab, 6144, MB(MB_TAB));
        }
        mb_expect(MB(MB_X + w), 4096);
        g2sx(sb + SM_D1 + w * 4096, x + (size_t)(128 * w + b) * 1024, 2048, MB(MB_X + w));
        g2sx(sb + SM_D1 + w * 4096 + 2048, x + (size_t)(128 * (w + 8) + b) * 1024, 2048, MB(MB_X + w));
    }
    __syncwarp();
    if (w == 0) asm volatile("bar.arrive 4, 256;" ::: "memory");
    asm volatile("setmaxnreg.inc.sync.aligned.u32 %0;" :: "n"(RCOMP));
    const bool nyq2 = (cg == 7 && w == 7);
    u32 nwr[2] = {0, 0}, nwi[2] = {0, 0};
    P2C kc;
    const u32 tb = sb + SM_TAB + lane * 16;
    if (w) asm volatile("bar.sync 4, 256;" ::: "memory");
    mb_wait(MB(MB_TAB), 0);
    ldt(tb, 0, kc.Fr[0], kc.Fr[1], kc.Fr[2], kc.Fr[3]);
    ldt(tb, 1, kc.Fi[0], kc.Fi[1], kc.Fi[2], kc.Fi[3]);
    ldt(tb, 2, kc.Fn[0], kc.Fn[1], kc.Fn[2], kc.Fn[3]);
    ldt(tb, 3, kc.T1c[0], kc.T1c[1], kc.T1s[0], kc.T1s[1]);
    u32 xk[2][8][2], dum;
    {
        u32 t2c[8][2], t2s[8][2], p8r, p8i, p8n, Pr[2], Pi[2];
        ldt(tb, 4, p8r, p8i, p8n, dum);
#pragma unroll
        for (int k0 = 1; k0 < 8; k0++) ldt(tb, 4 + k0, t2c[k0][0], t2c[k0][1], t2s[k0][0], t2s[k0][1]);
#pragma unroll
        for (int h = 0; h < 2; h++) {
            int ka = g + 8 * h, e = (g & 1) ? -256 : 256;
            tw2(ka * (256 * t4 + b) + e, ka * (256 * t4 + 128 + b) + e, 2048, 0.17677669529663687f, Pr[h], Pi[h]);
        }
        u32 zr[8][2], zi[8][2];
        mb_wait(MB(MB_X + w), 0);
        {
            u32 xa = sb + SM_D1 + w * 4096 + lane * 16;
#pragma unroll
            for (int t = 0; t < 8; t += 2) {
                ldsmt(zr[t][0], zr[t][1], zr[t + 1][0], zr[t + 1][1], xa + t * 256);
                ldsmt(zi[t][0], zi[t][1], zi[t + 1][0], zi[t + 1][1], xa + 2048 + t * 256);
            }
        }
        float mean[2], rs[2];
        row_stats2(zr, zi, g, t4, mean, rs);
        const float ra = rs[0] * 0.25f, rb = rs[1] * 0.25f, ma = -mean[0] * ra, mb_ = -mean[1] * rb;
#pragma unroll
        for (int t = 0; t < 8; t++)
#pragma unroll
            for (int h = 0; h < 2; h++) {
                zr[t][h] = pkh(fmaf(blo(zr[t][h]), ra, ma), fmaf(bhi(zr[t][h]), ra, ma));
                zi[t][h] = pkh(fmaf(blo(zi[t][h]), rb, mb_), fmaf(bhi(zi[t][h]), rb, mb_));
            }
        dft8(zr, zi, 0);
        dft8(zr, zi, 1);
#pragma unroll
        for (int k0 = 0; k0 < 8; k0++) {
            if (k0) { cmul(zr[k0][0], zi[k0][0], t2c[k0][0], t2s[k0][0]); cmul(zr[k0][1], zi[k0][1], t2c[k0][1], t2s[k0][1]); }
            u32 ur0, ur1, ui0, ui1;
            mma0(ur0, ur1, kc.Fr[0], kc.Fr[1], kc.Fr[2], kc.Fr[3], zr[k0][0], zr[k0][1]);
            mma0(ui0, ui1, kc.Fi[0], kc.Fi[1], kc.Fi[2], kc.Fi[3], zr[k0][0], zr[k0][1]);
            mma1(ur0, ur1, kc.Fn[0], kc.Fn[1], kc.Fn[2], kc.Fn[3], zi[k0][0], zi[k0][1]);
            mma1(ui0, ui1, kc.Fr[0], kc.Fr[1], kc.Fr[2], kc.Fr[3], zi[k0][0], zi[k0][1]);
            cmul(ur0, ui0, kc.T1c[0], kc.T1s[0]);
            cmul(ur1, ui1, kc.T1c[1], kc.T1s[1]);
            mma0(zr[k0][0], zr[k0][1], ur0, ur1, ui0, ui1, p8r, p8n);
            mma0(zi[k0][0], zi[k0][1], ur0, ur1, ui0, ui1, p8i, p8r);
        }
        {
            u32 eb = sb + SM_E + w * E_P;
#pragma unroll
            for (int h = 0; h < 2; h++) {
                int G = g + 8 * h + 16 * t4;
                u32 a0 = eb + gswz(G), a1 = eb + 2 * E_A + gswz(63 - G);
                sts128(a0, __byte_perm(zr[0][h], zr[1][h], 0x5410), __byte_perm(zr[2][h], zr[3][h], 0x5410), __byte_perm(zr[4][h], zr[5][h], 0x5410), __byte_perm(zr[6][h], zr[7][h], 0x5410));
                sts128(a0 + E_A, __byte_perm(zi[0][h], zi[1][h], 0x5410), __byte_perm(zi[2][h], zi[3][h], 0x5410), __byte_perm(zi[4][h], zi[5][h], 0x5410), __byte_perm(zi[6][h], zi[7][h], 0x5410));
                sts128(a1, zr[7][h], __byte_perm(zr[6][h], zr[5][h], 0x7632), __byte_perm(zr[4][h], zr[3][h], 0x7632), __byte_perm(zr[2][h], zr[1][h], 0x7632));
                sts128(a1 + E_A, zi[7][h], __byte_perm(zi[6][h], zi[5][h], 0x7632), __byte_perm(zi[4][h], zi[3][h], 0x7632), __byte_perm(zi[2][h], zi[1][h], 0x7632));
            }
            __syncwarp();
#pragma unroll
            for (int h = 0; h < 2; h++) {
                u32 a2 = eb + 2 * E_A + gswz(64 - (g + 8 * h + 16 * t4));
                sts16(a2, zr[0][h] >> 16);
                sts16(a2 + E_A, zi[0][h] >> 16);
            }
            if (lane == 0) {
                sts16(eb + 2 * E_A, zr[0][0]); sts16(eb + 3 * E_A, zi[0][0]);
                sts16(eb + 1024, zr[0][0] >> 16); sts16(eb + E_A + 1024, zi[0][0] >> 16);
            }
        }
        {
            u32 xa = sb + SM_D1 + w * 4096 + lane * 16;
#pragma unroll
            for (int t = 0; t < 8; t += 2) {
                ldsm(xk[0][t][0], xk[0][t][1], xk[0][t + 1][0], xk[0][t + 1][1], xa + t * 256);
                ldsm(xk[1][t][0], xk[1][t][1], xk[1][t + 1][0], xk[1][t + 1][1], xa + 2048 + t * 256);
            }
        }
        asm volatile("bar.sync 2, 288;" ::: "memory");
        {
            const u32 sg = (g & 1) ? 0x80008000u : 0u, ng = 0x80008000u;
            u32 la = sb + SM_E + (lane >> 3) * E_A + (lane & 7) * E_P;
            int kr = (lane & 7) + 8 * ((lane >> 3) & 1), cmp = lane >> 4;
            u32 sw = (u32)(((b & 1) | (((b >> 4) & 3) << 1)) ^ (lane & 7));
            u32 sa = sb + SM_D1 + (kr * 8 + w) * 128;
            u32 r[9][4];
#pragma unroll
            for (int i = 0; i < 9; i++) ldsmt(r[i][0], r[i][1], r[i][2], r[i][3], la + (i < 8 ? gswz(8 * w + i) : 1024u));
#pragma unroll
            for (int i = 0; i < 9; i++) {
                u32 o0, o1, p0, p1;
                mma0(o0, o1, Pr[0], Pr[1], Pi[0] ^ ng, Pi[1] ^ ng, r[i][0], r[i][1]);
                mma0(p0, p1, Pi[0], Pi[1], Pr[0], Pr[1], r[i][0], r[i][1]);
                mma1(o0, o1, Pi[0] ^ ng ^ sg, Pi[1] ^ ng ^ sg, Pr[0] ^ sg, Pr[1] ^ sg, r[i][2], r[i][3]);
                mma1(p0, p1, Pr[0] ^ sg, Pr[1] ^ sg, Pi[0] ^ sg, Pi[1] ^ sg, r[i][2], r[i][3]);
                if (i < 8) stsm(sa + (i >> 2) * 16384 + (((u32)(2 * (i & 3) + cmp)) ^ sw) * 16, o0, o1, p0, p1);
                else if (w == 7) stsm(mbb + MS_PART + kr * 32 + cmp * 16, o0, o1, p0, p1);
                if (i == 3) { fence_async(); __syncwarp(); if (lane == 0) mb_arrive(MB(MB_ST1)); }
            }
            fence_async();
            __syncwarp();
            if (lane == 0) mb_arrive(MB(MB_ST1 + 1));
        }
    }
    u32 wfr[8][2], wfi[8][2];
    int eloc;
    {
        mb_wait(MB(MB_W), 0);
        ldt(tb, 12, kc.f8r, kc.f8i, kc.f8n, dum);
        ldt(tb, 13, kc.Bc[0], kc.Bc[1], kc.Bs[0], kc.Bs[1]);
        u32 v[2][2][2][4];
#pragma unroll
        for (int a = 0; a < 2; a++)
#pragma unroll
            for (int h = 0; h < 2; h++)
#pragma unroll
                for (int e = 0; e < 2; e++) {
                    u32 ad = sb + SM_W + a * 18432 + (g + 8 * h + 16 * (2 * t4 + e)) * 144 + w * 8 + (k1a & 6) * 2, q[6];
#pragma unroll
                    for (int i = 0; i < 6; i++) q[i] = lds32(ad + 4 * (i % 3) + 64 * (i / 3));
#pragma unroll
                    for (int i = 0; i < 4; i++) v[a][h][e][i] = __funnelshift_r(q[i + (i >> 1)], q[i + (i >> 1) + 1], (k1a & 1) * 16);
                    if (nyq2) {
                        u32 nv = ((q[5] >> ((k1a & 1) * 16)) & 0xFFFFu) << (16 * e);
                        if (a) nwi[h] |= nv; else nwr[h] |= nv;
                    }
                }
        u32 mx = __vmaxu2(__vmaxu2(nwr[0] & 0x7FFF7FFFu, nwr[1] & 0x7FFF7FFFu), __vmaxu2(nwi[0] & 0x7FFF7FFFu, nwi[1] & 0x7FFF7FFFu));
#pragma unroll
        for (int i = 0; i < 32; i++) mx = __vmaxu2(mx, (&v[0][0][0][0])[i] & 0x7FFF7FFFu);
        mx = max(mx & 0xFFFFu, mx >> 16);
        mx = __reduce_max_sync(~0u, mx);
        eloc = min(max((int)(mx >> 7), 4), 253);
        const float sc = __int_as_float((254 - eloc) << 23);
#pragma unroll
        for (int c = 0; c < 8; c++)
#pragma unroll
            for (int h = 0; h < 2; h++) {
                if (c & 1) {
                    wfr[c][h] = pkh(bhi(v[0][h][0][c >> 1]) * sc, bhi(v[0][h][1][c >> 1]) * sc);
                    wfi[c][h] = pkh(bhi(v[1][h][0][c >> 1]) * sc, bhi(v[1][h][1][c >> 1]) * sc);
                } else {
                    wfr[c][h] = pkh(blo(v[0][h][0][c >> 1]) * sc, blo(v[0][h][1][c >> 1]) * sc);
                    wfi[c][h] = pkh(blo(v[1][h][0][c >> 1]) * sc, blo(v[1][h][1][c >> 1]) * sc);
                }
            }
#pragma unroll
        for (int h = 0; h < 2; h++) { nwr[h] = pkh(blo(nwr[h]) * sc, bhi(nwr[h]) * sc); nwi[h] = pkh(blo(nwi[h]) * sc, bhi(nwi[h]) * sc); }
        if (lane == 0) { sts32(mbb + MS_EXP + w * 4, eloc); mb_arrive(MB(MB_WC)); }
    }
    int eglob = 0;
    {
        u32 Gr[4], Gi[4], Gn[4];
#pragma unroll
        for (int hf = 0; hf < 2; hf++) {
            u32 zr[5][2], zi[5][2];
            mb_wait(MB(MB_IN2 + hf), 0);
            {
                u32 R[4][2], I[4][2];
                u32 sw = (u32)(((g & 1) | (t4 << 1)) ^ (k1a & 7));
#pragma unroll
                for (int u = 0; u < 4; u++) {
                    u32 a = sb + SM_E + hf * 16384 + (8 * (2 * t4 + (u & 1) + 8 * (u >> 1)) + g) * 128 + (w & 1) * 8;
                    lds64(R[u], a + (((u32)(w & 6)) ^ sw) * 16);
                    lds64(I[u], a + (((u32)(w | 1)) ^ sw) * 16);
                }
#define COLS4 _Pragma("unroll") for (int c = 0; c < 4; c++) { \
                    const u32 sel = (c & 1) ? 0x7632 : 0x5410; \
                    col_fwd(kc, __byte_perm(R[0][c >> 1], R[1][c >> 1], sel), __byte_perm(R[2][c >> 1], R[3][c >> 1], sel), \
                            __byte_perm(I[0][c >> 1], I[1][c >> 1], sel), __byte_perm(I[2][c >> 1], I[3][c >> 1], sel), wfr[4 * hf + c], wfi[4 * hf + c], zr[c], zi[c]); }
                if (hf && nyq2) {
                    u32 a = sb + SM_D0 + (16 * t4 + g) * 32;
                    col_fwd(kc, lds16(a) | (lds16(a + 256) << 16), lds16(a + 2048) | (lds16(a + 2304) << 16),
                            lds16(a + 16) | (lds16(a + 272) << 16), lds16(a + 2064) | (lds16(a + 2320) << 16), nwr, nwi, zr[4], zi[4]);
                    inv16(Gr, Gi, Gn, zr[4], zi[4]);
                    COLS4
#pragma unroll
                    for (int h = 0; h < 2; h++) {
                        a = sb + SM_D0 + 4096 + (8 * (g + 8 * h) + 2 * t4) * 32;
                        sts16(a, zr[4][h]); sts16(a + 16, zi[4][h]); sts16(a + 32, zr[4][h] >> 16); sts16(a + 48, zi[4][h] >> 16);
                    }
                } else {
                    COLS4
                }
            }
            if (hf == 0) {
                mb_wait(MB(MB_SC), 0);
                eglob = (int)lds32(mbb + MS_WIN + 4);
                int d = eloc - eglob;
                float f = d < -40 ? 0.f : __int_as_float((127 + d) << 23);
                u32 f2 = pkh(f, f);
#pragma unroll
                for (int i = 0; i < 4; i++) { Gr[i] = hmul(kc.Fr[i], f2); Gi[i] = hmul(kc.Fi[i], f2); Gn[i] = Gi[i] ^ 0x80008000u; }
            }
#pragma unroll
            for (int c = 0; c < 4; c++) inv16(Gr, Gi, Gn, zr[c], zi[c]);
            u32 sw = (u32)((t4 | ((g & 1) << 2)) ^ (k1a & 7));
#pragma unroll
            for (int h = 0; h < 2; h++)
#pragma unroll
                for (int e = 0; e < 2; e++) {
                    const u32 sel = e ? 0x7632 : 0x5410;
                    u32 a = sb + SM_D1 + hf * 16384 + (8 * (g + 8 * h) + 2 * t4 + e) * 128 + (w & 1) * 8;
                    sts64(a + (((u32)(w & 6)) ^ sw) * 16, __byte_perm(zr[0][h], zr[1][h], sel), __byte_perm(zr[2][h], zr[3][h], sel));
                    sts64(a + (((u32)(w | 1)) ^ sw) * 16, __byte_perm(zi[0][h], zi[1][h], sel), __byte_perm(zi[2][h], zi[3][h], sel));
                }
            fence_async();
            __syncwarp();
            if (lane == 0) mb_arrive(MB(MB_ST2 + hf));
        }
    }
    u32 rwk[8][2], t2c[8][2], t2s[8][2], p8r, p8i, p8n, Pr[2], Pi[2];
    ldt(tb, 14, p8r, p8i, p8n, dum);
#pragma unroll
    for (int k0 = 1; k0 < 8; k0++) ldt(tb, 14 + k0, t2c[k0][0], t2c[k0][1], t2s[k0][0], t2s[k0][1]);
#pragma unroll
    for (int t = 0; t < 8; t += 2) ldsm(rwk[t][0], rwk[t][1], rwk[t + 1][0], rwk[t + 1][1], tb + (SM_TAB2 - SM_TAB + 5120) + t * 256);
    float wsum = 0.f;
#pragma unroll
    for (int t = 0; t < 8; t++) wsum += (blo(rwk[t][0]) + bhi(rwk[t][0])) + (blo(rwk[t][1]) + bhi(rwk[t][1]));
#pragma unroll
    for (int o = 1; o < 32; o <<= 1) wsum += __shfl_xor_sync(~0u, wsum, o);
#pragma unroll
    for (int h = 0; h < 2; h++) {
        int ka = 2 * t4 + 8 * h;
        tw2(ka * (128 * g + b) + 256, (ka + 1) * (128 * g + b) - 256, 2048, 0.17677669529663687f * 0.5f, Pr[h], Pi[h]);
    }
    u32 hk[2][8][2], lk[2][8][2];
    u32 key;
    float mean[2], rs[2];
    {
        mb_wait(MB(MB_ST2 + 1), 0);
        {
            const u32 ng = 0x80008000u, se = 0x80000000u;
            int kr = (lane & 7) + 8 * ((lane >> 3) & 1), cmp = lane >> 4;
            u32 sw = (u32)(((b >> 1) & 7) ^ (lane & 7));
            u32 la = sb + SM_D1 + (w * 16 + kr) * 128;
            u32 sa = sb + SM_E + (lane >> 3) * E_A + (lane & 7) * E_P;
#pragma unroll
            for (int hf = 0; hf < 2; hf++) {
                mb_wait(MB(MB_IN3 + hf), 0);
                u32 r[5][4];
#pragma unroll
                for (int i = 0; i < 4 + hf; i++) ldsmt(r[i][0], r[i][1], r[i][2], r[i][3], i < 4 ? la + hf * 16384 + (((u32)(2 * i + cmp)) ^ sw) * 16 : mbb + MS_PART + kr * 32 + cmp * 16);
                if (hf) { __syncwarp(); if (lane == 0) mb_arrive(MB(MB_D1F)); }
#pragma unroll
                for (int i = 0; i < 4 + hf; i++) {
                    u32 o0, o1, p0, p1;
                    mma0(o0, o1, Pr[0], Pi[0] ^ ng, Pr[1], Pi[1] ^ ng, r[i][0], r[i][1]);
                    mma0(p0, p1, Pi[0] ^ ng ^ se, Pr[0] ^ se, Pi[1] ^ ng ^ se, Pr[1] ^ se, r[i][0], r[i][1]);
                    mma1(o0, o1, Pi[0], Pr[0], Pi[1], Pr[1], r[i][2], r[i][3]);
                    mma1(p0, p1, Pr[0] ^ se, Pi[0] ^ se, Pr[1] ^ se, Pi[1] ^ se, r[i][2], r[i][3]);
                    if (i < 4 || w == 7) stsm(sa + (i < 4 ? gswz(8 * w + 4 * hf + i) : 1024u), o0, o1, p0, p1);
                }
            }
        }
        bar_c();
        u32 zr[8][2], zi[8][2];
        {
            u32 eb = sb + SM_E + w * E_P;
#pragma unroll
            for (int h = 0; h < 2; h++)
#pragma unroll
                for (int c = 0; c < 2; c++) {
                    int G = g + 8 * h + 16 * t4;
                    u32 P[4], M[4];
                    lds128(P, eb + c * E_A + gswz(G));
                    lds128(M, eb + (2 + c) * E_A + gswz(63 - G));
                    u32 m0 = lds16(eb + (2 + c) * E_A + gswz(64 - G));
                    u32 z0 = __byte_perm(P[0], m0, 0x5410);
                    if (h == 0) {
                        u32 o = lds16(eb + (2 + c) * E_A) | (lds16(eb + c * E_A + 1024) << 16);
                        u32 av = hmul(hadd(z0, o), 0x38003800u);
                        if (lane == 0) z0 = av;
                    }
                    u32 (&z)[8][2] = c ? zi : zr;
                    z[0][h] = z0;
                    z[1][h] = __byte_perm(P[0], M[3], 0x7632); z[2][h] = __byte_perm(P[1], M[3], 0x5410);
                    z[3][h] = __byte_perm(P[1], M[2], 0x7632); z[4][h] = __byte_perm(P[2], M[2], 0x5410);
                    z[5][h] = __byte_perm(P[2], M[1], 0x7632); z[6][h] = __byte_perm(P[3], M[1], 0x5410);
                    z[7][h] = __byte_perm(P[3], M[0], 0x7632);
                }
        }
#pragma unroll
        for (int k0 = 0; k0 < 8; k0++) {
#pragma unroll
            for (int h = 0; h < 2; h++) {
                u32 a, c;
                mma0(a, c, p8r, p8n, p8i, p8r, zr[k0][h], zi[k0][h]);
                cmulc(a, c, kc.Bc[h], kc.Bs[h]);
                zr[k0][h] = a; zi[k0][h] = c;
            }
            inv16(kc.Fr, kc.Fi, kc.Fn, zr[k0], zi[k0]);
            if (k0) { cmulc(zr[k0][0], zi[k0][0], t2c[k0][0], t2s[k0][0]); cmulc(zr[k0][1], zi[k0][1], t2c[k0][1], t2s[k0][1]); }
        }
        dft8(zi, zr, 0);
        dft8(zi, zr, 1);
        const u32 ys = (u32)(eglob - 1) * 0x00800080u;
#pragma unroll
        for (int t = 0; t < 8; t++)
#pragma unroll
            for (int h = 0; h < 2; h++) {
                float2 fa = __half22float2(H(zr[t][h])), fb = __half22float2(H(zi[t][h]));
                hk[0][t][h] = bfma(pkb(fa.x, fa.y), ys, xk[0][t][h]);
                hk[1][t][h] = bfma(pkb(fb.x, fb.y), ys, xk[1][t][h]);
            }
        float c[4] = {0.f, 0.f, 0.f, 0.f}, c2[4] = {0.f, 0.f, 0.f, 0.f}, dot[2];
#pragma unroll
        for (int t = 0; t < 8; t++) mmab((t & 1) ? c2 : c, hk[0][t][0], hk[1][t][0], hk[0][t][1], hk[1][t][1], rwk[t][0], rwk[t][1]);
        const bool dg = (t4 == (g >> 1));
        dot[0] = dg ? ((g & 1) ? c[1] + c2[1] : c[0] + c2[0]) : 0.f;
        dot[1] = dg ? ((g & 1) ? c[3] + c2[3] : c[2] + c2[2]) : 0.f;
        row_stats2(hk[0], hk[1], g, t4, mean, rs, dot);
        const float r0 = rs[0] * (dot[0] - mean[0] * wsum), r1 = rs[1] * (dot[1] - mean[1] * wsum);
        u32 rb = pkb(r0, r1), ka = rb & 0xFFFFu, kb = rb >> 16;
        ka = (ka & 0x8000u) ? (~ka & 0xFFFFu) : (ka | 0x8000u);
        kb = (kb & 0x8000u) ? (~kb & 0xFFFFu) : (kb | 0x8000u);
        key = max((ka << 16) | (u32)(2047 - (128 * w + b)), (kb << 16) | (u32)(2047 - (128 * (w + 8) + b)));
        if (lane == 0) { sts32(mbb + MS_KEY + w * 4, key); mb_arrive(MB(MB_KEY)); }
    }
#pragma unroll
    for (int r = 0; r < 2; r++) {
        const float rh = rbf(rs[r]);
        u32 m2 = pkb(mean[r], mean[r]), rh2 = pkb(rh, rh), rl2 = pkb(rs[r] - rh, rs[r] - rh);
#pragma unroll
        for (int t = 0; t < 8; t++)
#pragma unroll
            for (int h = 0; h < 2; h++) { u32 d = bsub(hk[r][t][h], m2); lk[r][t][h] = bfma(d, rh2, bmul(d, rl2)); }
    }
    mb_wait(MB(MB_KEY), 0);
    {
        u32 k4[4], k5[4];
        lds128(k4, mbb + MS_KEY); lds128(k5, mbb + MS_KEY + 16);
        u32 best = max(max(max(k4[0], k4[1]), max(k4[2], k4[3])), max(max(k5[0], k5[1]), max(k5[2], k5[3])));
        if (key == best) {
            const u32 ea = sb + SM_E + w * 2048 + lane * 16;
            if ((2047 - (int)(best & 0xFFFFu)) >= 1024) {
#pragma unroll
                for (int t = 0; t < 8; t += 2) {
                    stsm(ea + t * 256, lk[1][t][0], lk[1][t][1], lk[1][t + 1][0], lk[1][t + 1][1]);
                    stsm(ea + 16384 + t * 256, hk[1][t][0], hk[1][t][1], hk[1][t + 1][0], hk[1][t + 1][1]);
                }
            } else {
#pragma unroll
                for (int t = 0; t < 8; t += 2) {
                    stsm(ea + t * 256, lk[0][t][0], lk[0][t][1], lk[0][t + 1][0], lk[0][t + 1][1]);
                    stsm(ea + 16384 + t * 256, hk[0][t][0], hk[0][t][1], hk[0][t + 1][0], hk[0][t + 1][1]);
                }
            }
            __syncwarp();
            u32 rv[8][4];
#pragma unroll
            for (int i = 0; i < 8; i++) lds128(rv[i], ea + (i >> 2) * 16384 + (i & 3) * 512);
#pragma unroll
            for (int i = 0; i < 8; i++) __stcg(reinterpret_cast<uint4*>(gs->cand + b * 1024) + 32 * i + lane, make_uint4(rv[i][0], rv[i][1], rv[i][2], rv[i][3]));
            __syncwarp();
        }
        u32 eb = sb + SM_E + w * 2048 + lane * 16;
#pragma unroll
        for (int r = 0; r < 2; r++)
#pragma unroll
            for (int t = 0; t < 8; t += 2)
                stsm(eb + r * 16384 + t * 256, badd(hk[r][t][0], lk[r][t][0]), badd(hk[r][t][1], lk[r][t][1]),
                     badd(hk[r][t + 1][0], lk[r][t + 1][0]), badd(hk[r][t + 1][1], lk[r][t + 1][1]));
        fence_async();
        __syncwarp();
        if (lane == 0) mb_arrive(MB(MB_OUT));
    }
    u32 A[8][4][4], D[8][2][4];
    if (b < NFFN) {
        mb_wait(MB(MB_GU), 0);
        int r = (w & 1) * 128 + (lane & 7) + 8 * (lane >> 4);
        u32 a0 = sb + SM_GU + (w >> 1) * 16384 + r * 64;
        u32 ch = (lane >> 3) & 1, sw = (lane >> 1) & 3;
#pragma unroll
        for (int ks = 0; ks < 8; ks++)
#pragma unroll
            for (int mt = 0; mt < 4; mt++)
                ldsmt(A[ks][mt][0], A[ks][mt][1], A[ks][mt][2], A[ks][mt][3], a0 + (mt >> 1) * 65536 + ks * 1024 + (((ch + 2 * (mt & 1)) ^ sw) * 16));
    }
    mb_wait(MB(MB_AM), 0);
    if (b < NFFN) {
        u32 xb[8][2];
        const u32 xs = mbb + MS_PART + w * 256;
#pragma unroll
        for (int ks = 0; ks < 8; ks += 2) ldsm(xb[ks][0], xb[ks][1], xb[ks + 1][0], xb[ks + 1][1], xs + ks * 32 + (lane >> 3) * 16);
        float c[8][4];
#pragma unroll
        for (int mt = 0; mt < 8; mt++) { c[mt][0] = c[mt][1] = c[mt][2] = c[mt][3] = 0.f; }
#pragma unroll
        for (int ks = 0; ks < 8; ks++) {
#pragma unroll
            for (int mt = 0; mt < 4; mt++) mmab(c[mt + 4 * (ks & 1)], A[ks][mt][0], A[ks][mt][1], A[ks][mt][2], A[ks][mt][3], xb[ks][0], xb[ks][1]);
        }
        float s0 = t4 == 0 ? c[0][0] + c[4][0] : t4 == 1 ? c[1][0] + c[5][0] : t4 == 2 ? c[2][0] + c[6][0] : c[3][0] + c[7][0];
        float s1 = t4 == 0 ? c[0][2] + c[4][2] : t4 == 1 ? c[1][2] + c[5][2] : t4 == 2 ? c[2][2] + c[6][2] : c[3][2] + c[7][2];
        sts32(sb + SM_GU + w * 8192 + (t4 * 16 + g) * 4, __float_as_uint(s0));
        sts32(sb + SM_GU + w * 8192 + (t4 * 16 + g + 8) * 4, __float_as_uint(s1));
    }
    if (b < NFFN) {
        bar_c();
        float gv = 0.f, us = 0.f;
#pragma unroll
        for (int i = 0; i < 8; i++) {
            gv += __uint_as_float(lds32(sb + SM_GU + i * 8192 + lane * 4));
            us += __uint_as_float(lds32(sb + SM_GU + i * 8192 + 128 + lane * 4));
        }
#define DLOAD { mb_wait(MB(MB_DN), 0); \
            const u32 da = sb + SM_D0 + w * 8192 + ((lane & 7) + 8 * (lane >> 4)) * 128, dch = (lane >> 3) & 1, dsw = lane & 7; \
            _Pragma("unroll") for (int i = 0; i < 16; i++) \
                ldsmt(D[i >> 1][i & 1][0], D[i >> 1][i & 1][1], D[i >> 1][i & 1][2], D[i >> 1][i & 1][3], da + (i >> 3) * 4096 + (i & 1) * 2048 + (((dch + 2 * ((i >> 1) & 3)) ^ dsw) * 16)); }
        gv = rbf(gv);
        float hid = rbf(__fdividef(gv, 1.f + __expf(-gv))) * rbf(us);
        u32 hp = pkb(hid, __shfl_down_sync(~0u, hid, 1));
        u32 hb[4];
#pragma unroll
        for (int i = 0; i < 4; i++) hb[i] = __shfl_sync(~0u, hp, 8 * i + 2 * t4);
        DLOAD
        float c[8][4];
#pragma unroll
        for (int mt = 0; mt < 8; mt++) {
            c[mt][0] = c[mt][1] = c[mt][2] = c[mt][3] = 0.f;
            mmab(c[mt], D[mt][0][0], D[mt][0][1], D[mt][0][2], D[mt][0][3], hb[0], hb[1]);
            mmab(c[mt], D[mt][1][0], D[mt][1][1], D[mt][1][2], D[mt][1][3], hb[2], hb[3]);
        }
#pragma unroll
        for (int i = 0; i < 4; i++) {
            float v = t4 == 0 ? c[2 * i][0] : t4 == 1 ? c[2 * i][2] : t4 == 2 ? c[2 * i + 1][0] : c[2 * i + 1][2];
            __stcg(gs->part + ((16 * w + 4 * i + t4) * NFFN + b) * 8 + g, v);
        }
    }
    __syncwarp();
    if (lane == 0) mb_arrive(MB(MB_PS));
    }
}

typedef CUresult (*PFN_enc)(CUtensorMap*, CUtensorMapDataType, cuuint32_t, void*, const cuuint64_t*, const cuuint64_t*,
                            const cuuint32_t*, const cuuint32_t*, CUtensorMapInterleave, CUtensorMapSwizzle,
                            CUtensorMapL2promotion, CUtensorMapFloatOOBfill);

static void make_map(PFN_enc enc, CUtensorMap* m, void* p, uint64_t d0, uint64_t d1, uint64_t pitch, uint32_t b0, uint32_t b1, CUtensorMapSwizzle sw,
                     uint64_t d2 = 0, uint64_t pitch2 = 0, uint32_t b2 = 0) {
    cuuint64_t dims[3] = {d0, d1, d2}, strides[2] = {pitch, pitch2};
    cuuint32_t box[3] = {b0, b1, b2}, es[3] = {1, 1, 1};
    enc(m, CU_TENSOR_MAP_DATA_TYPE_BFLOAT16, d2 ? 3 : 2, p, dims, strides, box, es, CU_TENSOR_MAP_INTERLEAVE_NONE, sw,
        CU_TENSOR_MAP_L2_PROMOTION_NONE, CU_TENSOR_MAP_FLOAT_OOB_FILL_NONE);
}

extern "C" void kernel_launch(void* const* d_in, const int* in_sizes, int n_in, void* d_out, int out_size) {
    static PFN_enc enc = nullptr;
    static Scratch* gs = nullptr;
    static void* tab = nullptr;
    if (!enc) {
        cudaDriverEntryPointQueryResult qr;
        void* fn = nullptr;
        cudaGetDriverEntryPoint("cuTensorMapEncodeTiled", &fn, cudaEnableDefault, &qr);
        enc = (PFN_enc)fn;
        cudaGetSymbolAddress((void**)&gs, g_s);
        cudaGetSymbolAddress(&tab, g_tab);
        cudaFuncSetAttribute(fused_kernel, cudaFuncAttributeMaxDynamicSharedMemorySize, SM_TOTAL);
    }
    CUtensorMap twr, twi, tg, tu, td, s1, s2, n1, n2, to;
    make_map(enc, &to, d_out, 256, 512, 512, 256, 4, CU_TENSOR_MAP_SWIZZLE_NONE, 16, 262144, 16);
    make_map(enc, &s1, gs->s1, 8192, 8, 16384, 64, 8, CU_TENSOR_MAP_SWIZZLE_NONE, 32, 131072, 16);
    make_map(enc, &s2, gs->s2, 8192, 256, 16384, 64, 128, CU_TENSOR_MAP_SWIZZLE_NONE);
    make_map(enc, &n1, gs->n1, 2048, 16, 4096, 16, 16, CU_TENSOR_MAP_SWIZZLE_NONE);
    make_map(enc, &n2, gs->n2, 256, 128, 512, 16, 128, CU_TENSOR_MAP_SWIZZLE_NONE);
    make_map(enc, &twr, d_in[1], 8208, 128, 16416, 72, 128, CU_TENSOR_MAP_SWIZZLE_NONE);
    make_map(enc, &twi, d_in[2], 8208, 128, 16416, 72, 128, CU_TENSOR_MAP_SWIZZLE_NONE);
    make_map(enc, &tg, d_in[5], 3584, 1024, 7168, 32, 64, CU_TENSOR_MAP_SWIZZLE_64B);
    make_map(enc, &tu, d_in[6], 3584, 1024, 7168, 32, 64, CU_TENSOR_MAP_SWIZZLE_64B);
    make_map(enc, &td, d_in[7], 64, 3584, 2048, 64, 32, CU_TENSOR_MAP_SWIZZLE_128B, 16, 128, 4);
    fused_kernel<<<NCTA, NTHR, SM_TOTAL, cudaStreamPerThread>>>(
        (const __nv_bfloat16*)d_in[0], (const __nv_bfloat16*)d_in[4],
        (__nv_bfloat16*)d_out, gs, (const uint4*)tab,
        s1, s2, n1, n2, to, twr, twi, tg, tu, td);
}
```
